```python
import torch

def _softmax(x, axis=-1):
    return torch.softmax(x, dim=axis)
def _gelu(x):
    return torch.nn.functional.gelu(x, approximate="tanh")
def _silu(x):
    return torch.nn.functional.silu(x)
def _sigmoid(x):
    return torch.sigmoid(x)
def _layernorm(x, axis=-1, eps=1e-5):
    m = x.mean(dim=axis, keepdim=True)
    v = x.var(dim=axis, keepdim=True, unbiased=False)
    return (x - m) / torch.sqrt(v + eps)
def _scatter_add(tgt, idx, src, axis=0):
    return tgt.clone().index_add_(axis, idx, src)
def _segment_sum(src, seg, n):
    out = torch.zeros((n,) + src.shape[1:], dtype=src.dtype)
    return out.index_add_(0, seg, src)
def _pad(x, pw):
    flat = tuple(v for pair in reversed(pw) for v in pair)
    return torch.nn.functional.pad(x, flat)

kernel_name = 'sequential_preLN__sliding_block__glu_gated_reglu__prompt'

def setup_inputs():

    _w = (lambda a: (lambda t: t.to(torch.bfloat16) if t.is_floating_point() else t)(torch.as_tensor(a)))
    def _A_setup():
        B, S, D = 1, 2048, 512
        return {
            "x": _w((lambda *s: torch.randn(*s, dtype=torch.bfloat16) * 0.05)(B, S, D)),
            "wqkv": _w((lambda *s: torch.randn(*s, dtype=torch.bfloat16) * 0.05)(D, 3 * D)),
            "wo": _w((lambda *s: torch.randn(*s, dtype=torch.bfloat16) * 0.05)(D, D)),
        }
    _A_in = _A_setup()

    def _B_setup():
        B, S, D, F = 1, 2048, 512, 1792
        return {
            "x": _w((lambda *s: torch.randn(*s, dtype=torch.bfloat16) * 0.05)(B, S, D)),
            "W_gate": _w((lambda *s: torch.randn(*s, dtype=torch.bfloat16) * 0.8)(D, F) * (2.0 / D) ** 0.5),
            "W_up": _w((lambda *s: torch.randn(*s, dtype=torch.bfloat16) * 0.8)(D, F) * (2.0 / D) ** 0.5),
            "W_down": _w((lambda *s: torch.randn(*s, dtype=torch.bfloat16) * 0.8)(F, D) * (1.0 / F) ** 0.5),
        }
    _B_in = _B_setup()

    return {
        "A_x": _A_in["x"],
        "A_wqkv": _A_in["wqkv"],
        "A_wo": _A_in["wo"],
        "B_x": _B_in["x"],
        "B_W_gate": _B_in["W_gate"],
        "B_W_up": _B_in["W_up"],
        "B_W_down": _B_in["W_down"],
    }

def reference(A_x, A_wqkv, A_wo, B_x, B_W_gate, B_W_up, B_W_down):
    def _A_ref(x, wqkv, wo):
        B, S, D = x.shape
        H = 32; Dh = D // H; W = 256
        qkv = (lambda x, *d: x.permute(*d))((x @ wqkv).reshape(B, S, 3, H, Dh), 2, 0, 3, 1, 4)
        q, k, v = qkv[0], qkv[1], qkv[2]
        scores = torch.einsum("bhqd,bhkd->bhqk", q, k) * (Dh ** -0.5)
        idx = torch.arange(S)
        mask = (idx[:, None] - idx[None, :] >= 0) & (idx[:, None] - idx[None, :] < W)
        scores = torch.where(mask[None, None], scores, -1e9)
        p = _softmax(scores, axis=-1)
        o = torch.einsum("bhqk,bhkd->bhqd", p, v)
        return (lambda x, *d: x.permute(*d))(o, 0, 2, 1, 3).reshape(B, S, D) @ wo

    def _B_ref(x, W_gate, W_up, W_down):
        gate = torch.einsum("bsd,df->bsf", x, W_gate)
        up = torch.einsum("bsd,df->bsf", x, W_up)
        gate = gate * (lambda x, dt: x.to(dt))(gate > 0, gate.dtype)
        h = gate * up
        return torch.einsum("bsf,fd->bsd", h, W_down)

    x = A_x
    h = x + _A_ref(_layernorm(x, axis=-1), A_wqkv, A_wo)
    h2 = h + _B_ref(_layernorm(h, axis=-1), B_W_gate, B_W_up, B_W_down)
    return h2
```

```cpp
#include <cuda_runtime.h>
#include <cuda_bf16.h>
#include <cuda.h>
#include <stdint.h>
#include <limits.h>

namespace {

constexpr int DM = 512, FF = 1792;
constexpr int NBLK = 16, NJ = 8, NCTA = NBLK * NJ;
constexpr int STAGE_BYTES = 16384;
constexpr int SM_K = 8 * STAGE_BYTES;
constexpr int SM_V = SM_K + 49152;
constexpr int SM_BAR = SM_V + 49152;
constexpr int SMEM_BYTES = SM_BAR + 1536;

constexpr int B_FULL = 0, B_EMPTY = 64, B_X = 128, B_XCH = 192, B_K = 256, B_V = 288, B_XFREE = 320, B_DEAD = 328, B_PUB = 344, B_S5 = 376, B_WG = 384, B_LVL = 624;
constexpr int W_INO = 0, W_INH = 24, W_INA = 48, W_ODEAD = 96, W_HDEAD = 104;
#define HORDER 1
#define SKEW 0
constexpr uint32_t SMD = 1024;

struct Params {
    CUtensorMap xm, qkv, wo, wg, wu, wg2, wu2, wd, wd2, om;
    uint32_t zero;
};

extern __shared__ __align__(1024) uint8_t smem_raw[];

struct Scratch {
    uint4 kv[NCTA * 2 * 4 * 8 * 32];
    uint4 o[NBLK * 8 * 32 * 32];
    uint4 h[NBLK * 8 * 32 * 32];
    uint4 stat[NBLK * 8 * 8 * 8];
};
__device__ Scratch g_scr[2];
__device__ uint4 g_hff[NCTA * 2 * 4 * 512];
__device__ unsigned g_flagF[NCTA * 32];
__device__ unsigned g_epoch[NCTA * 32];
#define PROF(n) do {} while (0)

__device__ __forceinline__ uint32_t smem_u32(const void* p) { return (uint32_t)__cvta_generic_to_shared(p); }
__device__ __forceinline__ void mbar_init(uint32_t b, uint32_t c) {
    asm volatile("mbarrier.init.shared::cta.b64 [%0], %1;" ::"r"(b), "r"(c) : "memory");
}
__device__ __forceinline__ void mbar_expect(uint32_t b, uint32_t bytes) {
    asm volatile("mbarrier.arrive.expect_tx.shared::cta.b64 _, [%0], %1;" ::"r"(b), "r"(bytes) : "memory");
}
__device__ __forceinline__ void mbar_arrive(uint32_t b) {
    asm volatile("mbarrier.arrive.shared::cta.b64 _, [%0];" ::"r"(b) : "memory");
}
__device__ __forceinline__ void mbar_wait(uint32_t b, uint32_t ph) {
    asm volatile(
        "{\n.reg .pred p;\n.reg .u32 n;\n"
        "mov.u32 n, 0;\n"
        "LOOP:\n"
        "mbarrier.try_wait.parity.shared::cta.b64 p, [%0], %1;\n"
        "add.u32 n, n, 1;\n"
        "setp.lt.and.u32 p, n, 262144, !p;\n"
        "@p bra LOOP;\n}"
        ::"r"(b), "r"(ph) : "memory");
}
__device__ __forceinline__ unsigned ld_acquire(const unsigned* p) {
    unsigned v;
    asm volatile("ld.acquire.gpu.global.u32 %0, [%1];" : "=r"(v) : "l"(p) : "memory");
    return v;
}
__device__ __forceinline__ void flag_set(unsigned* p, unsigned v) {
    asm volatile("st.relaxed.gpu.global.u32 [%0], %1;" ::"l"(p), "r"(v) : "memory");
}
__device__ __forceinline__ uint4 ld_ll(const uint4* p) {
    uint4 v;
    asm volatile("ld.relaxed.gpu.global.v4.u32 {%0,%1,%2,%3}, [%4];" : "=r"(v.x), "=r"(v.y), "=r"(v.z), "=r"(v.w) : "l"(p) : "memory");
    return v;
}
__device__ __forceinline__ uint32_t ld_ll1(const uint32_t* p) {
    uint32_t v;
    asm volatile("ld.relaxed.gpu.global.u32 %0, [%1];" : "=r"(v) : "l"(p) : "memory");
    return v;
}
__device__ __forceinline__ void ld_ll4(uint32_t (&r)[4], const uint4* p) {
    asm volatile("ld.relaxed.gpu.global.v4.u32 {%0,%1,%2,%3}, [%4];" : "=r"(r[0]), "=r"(r[1]), "=r"(r[2]), "=r"(r[3]) : "l"(p) : "memory");
}
__device__ __forceinline__ void st_ll(uint4* p, uint32_t a, uint32_t b, uint32_t c, uint32_t d) {
    asm volatile("st.relaxed.gpu.global.v4.u32 [%0], {%1,%2,%3,%4};" ::"l"(p), "r"(a), "r"(b), "r"(c), "r"(d) : "memory");
}
constexpr int SPIN_LIMIT = 100000;
__device__ __forceinline__ uint32_t nz(uint32_t v) { return max(v, 1u); }
__device__ __forceinline__ uint32_t umin4(uint32_t m, const uint32_t (&r)[4]) {
    return __vimin3_u32(__vimin3_u32(m, r[0], r[1]), r[2], r[3]);
}
__device__ __forceinline__ uint32_t umin4(uint32_t m, const uint4& r) { return __vimin3_u32(__vimin3_u32(m, r.x, r.y), r.z, r.w); }
__device__ __forceinline__ bool warp_bad(uint32_t m) { return __any_sync(0xffffffffu, m == 0); }
template <int T0, int ID>
__device__ __forceinline__ void validate8(uint32_t (&a)[32][4], const uint4* src) {
#pragma unroll 1
    for (int it = 0; it < SPIN_LIMIT; it++) {
        uint32_t m0 = 0xffffffffu, m1 = 0xffffffffu;
#pragma unroll
        for (int k = 0; k < 4; k++) { m0 = umin4(m0, a[T0 + k]); m1 = umin4(m1, a[T0 + 4 + k]); }
        if (!warp_bad(min(m0, m1))) break;
#pragma unroll
        for (int k = 0; k < 8; k++) ld_ll4(a[T0 + k], src + k * 32);
    }
}
__device__ __forceinline__ void bulk_g2s(uint32_t dst, const void* src, uint32_t bytes, uint32_t bar) {
    asm volatile("cp.async.bulk.shared::cluster.global.mbarrier::complete_tx::bytes [%0], [%1], %2, [%3];"
                 ::"r"(dst), "l"(src), "r"(bytes), "r"(bar) : "memory");
}
__device__ __forceinline__ void bulk_s2g(void* dst, uint32_t src, uint32_t bytes) {
    asm volatile("cp.async.bulk.global.shared::cta.bulk_group [%0], [%1], %2;" ::"l"(dst), "r"(src), "r"(bytes) : "memory");
}
__device__ __forceinline__ void cp_async16(uint32_t dst, const void* src) {
    asm volatile("cp.async.cg.shared.global [%0], [%1], 16;" ::"r"(dst), "l"(src) : "memory");
}
__device__ __forceinline__ void lds4(uint32_t (&r)[4], uint32_t addr) {
    asm volatile("ld.shared.v4.u32 {%0,%1,%2,%3}, [%4];" : "=r"(r[0]), "=r"(r[1]), "=r"(r[2]), "=r"(r[3]) : "r"(addr) : "memory");
}
__device__ __forceinline__ void ld_cg4(uint32_t (&r)[4], const uint4* p) {
    asm volatile("ld.global.cg.v4.u32 {%0,%1,%2,%3}, [%4];" : "=r"(r[0]), "=r"(r[1]), "=r"(r[2]), "=r"(r[3]) : "l"(p) : "memory");
}
__device__ __forceinline__ void stg128(uint4* p, uint32_t a, uint32_t b, uint32_t c, uint32_t d) {
    asm volatile("st.global.v4.u32 [%0], {%1,%2,%3,%4};" ::"l"(p), "r"(a), "r"(b), "r"(c), "r"(d) : "memory");
}
__device__ __forceinline__ uint32_t mapa(uint32_t addr, uint32_t rank) {
    uint32_t r;
    asm("mapa.shared::cluster.u32 %0, %1, %2;" : "=r"(r) : "r"(addr), "r"(rank));
    return r;
}
__device__ __forceinline__ void st_async4(uint32_t addr, uint32_t bar, uint32_t a, uint32_t b, uint32_t c, uint32_t d) {
    asm volatile("st.async.shared::cluster.mbarrier::complete_tx::bytes.v4.b32 [%0], {%2,%3,%4,%5}, [%1];"
                 ::"r"(addr), "r"(bar), "r"(a), "r"(b), "r"(c), "r"(d) : "memory");
}
__device__ __forceinline__ void stsm4(uint32_t addr, uint32_t a, uint32_t b, uint32_t c, uint32_t d) {
    asm volatile("stmatrix.sync.aligned.m8n8.x4.shared.b16 [%0], {%1,%2,%3,%4};" ::"r"(addr), "r"(a), "r"(b), "r"(c), "r"(d) : "memory");
}
__device__ __forceinline__ void tma_store2d(const CUtensorMap* tm, uint32_t src, int c0, int c1) {
    asm volatile("cp.async.bulk.tensor.2d.global.shared::cta.bulk_group [%0, {%2,%3}], [%1];" ::"l"(tm), "r"(src), "r"(c0), "r"(c1) : "memory");
}
__device__ __forceinline__ void mbar_wait_cluster(uint32_t b, uint32_t ph) {
    asm volatile(
        "{\n.reg .pred p;\n.reg .u32 n;\n"
        "mov.u32 n, 0;\n"
        "LOOP:\n"
        "mbarrier.try_wait.parity.acquire.cluster.shared::cta.b64 p, [%0], %1;\n"
        "add.u32 n, n, 1;\n"
        "setp.lt.and.u32 p, n, 262144, !p;\n"
        "@p bra LOOP;\n}"
        ::"r"(b), "r"(ph) : "memory");
}
__device__ __forceinline__ uint32_t tie(uint32_t x, uint32_t dep, uint32_t zero) {
    uint32_t r;
    asm("lop3.b32 %0, %1, %2, %3, 0xF8;" : "=r"(r) : "r"(x), "r"(dep), "r"(zero));
    return r;
}
__device__ __forceinline__ float tie(float x, int dep, uint32_t zero) { return __uint_as_float(tie(__float_as_uint(x), (uint32_t)dep, zero)); }
__device__ __forceinline__ void ldsm4(uint32_t (&r)[4], uint32_t addr) {
    asm volatile("ldmatrix.sync.aligned.m8n8.x4.shared.b16 {%0,%1,%2,%3}, [%4];"
                 : "=r"(r[0]), "=r"(r[1]), "=r"(r[2]), "=r"(r[3]) : "r"(addr) : "memory");
}
__device__ __forceinline__ void sts128(uint32_t addr, uint32_t a, uint32_t b, uint32_t c, uint32_t d) {
    asm volatile("st.shared.v4.u32 [%0], {%1,%2,%3,%4};" ::"r"(addr), "r"(a), "r"(b), "r"(c), "r"(d) : "memory");
}
__device__ __forceinline__ uint4 lds128(uint32_t addr) {
    uint4 v;
    asm volatile("ld.shared.v4.u32 {%0,%1,%2,%3}, [%4];" : "=r"(v.x), "=r"(v.y), "=r"(v.z), "=r"(v.w) : "r"(addr) : "memory");
    return v;
}
__device__ __forceinline__ void tma2d(uint32_t dst, const CUtensorMap* tm, uint32_t bar, int c0, int c1) {
    asm volatile("cp.async.bulk.tensor.2d.shared::cluster.global.mbarrier::complete_tx::bytes [%0], [%1, {%3,%4}], [%2];"
                 ::"r"(dst), "l"(tm), "r"(bar), "r"(c0), "r"(c1) : "memory");
}
__device__ __forceinline__ void prefetch_tmap(const CUtensorMap* tm) {
    asm volatile("prefetch.tensormap [%0];" ::"l"(tm) : "memory");
}
__device__ __forceinline__ uint32_t pack_bf16(float lo, float hi) {
    uint32_t r;
    asm("cvt.rn.bf16x2.f32 %0, %1, %2;" : "=r"(r) : "f"(hi), "f"(lo));
    return r;
}
__device__ __forceinline__ float bf_lo(uint32_t v) { return __uint_as_float(v << 16); }
__device__ __forceinline__ float bf_hi(uint32_t v) { return __uint_as_float(v & 0xffff0000u); }
__device__ __forceinline__ uint32_t badd2(uint32_t a, uint32_t b) {
    uint32_t r;
    asm("add.rn.bf16x2 %0, %1, %2;" : "=r"(r) : "r"(a), "r"(b));
    return r;
}
__device__ __forceinline__ float ex2(float x) {
    float r;
    asm("ex2.approx.ftz.f32 %0, %1;" : "=f"(r) : "f"(x));
    return r;
}
__device__ __forceinline__ float rcp(float x) {
    float r;
    asm("rcp.approx.ftz.f32 %0, %1;" : "=f"(r) : "f"(x));
    return r;
}
__device__ __forceinline__ uint32_t movtrans(uint32_t v) {
    uint32_t r;
    asm volatile("movmatrix.sync.aligned.m8n8.trans.b16 %0, %1;" : "=r"(r) : "r"(v));
    return r;
}
__device__ __forceinline__ void mma16816(float& d0, float& d1, float& d2, float& d3, uint32_t a0, uint32_t a1, uint32_t a2,
                                         uint32_t a3, uint32_t b0, uint32_t b1) {
    asm("mma.sync.aligned.m16n8k16.row.col.f32.bf16.bf16.f32 {%0,%1,%2,%3},{%4,%5,%6,%7},{%8,%9},{%0,%1,%2,%3};"
        : "+f"(d0), "+f"(d1), "+f"(d2), "+f"(d3) : "r"(a0), "r"(a1), "r"(a2), "r"(a3), "r"(b0), "r"(b1));
}
__device__ __forceinline__ void mma16816_z(float& d0, float& d1, float& d2, float& d3, uint32_t a0, uint32_t a1, uint32_t a2,
                                           uint32_t a3, uint32_t b0, uint32_t b1) {
    asm("mma.sync.aligned.m16n8k16.row.col.f32.bf16.bf16.f32 {%0,%1,%2,%3},{%4,%5,%6,%7},{%8,%9},{%10,%10,%10,%10};"
        : "=f"(d0), "=f"(d1), "=f"(d2), "=f"(d3) : "r"(a0), "r"(a1), "r"(a2), "r"(a3), "r"(b0), "r"(b1), "f"(0.f));
}
__device__ __forceinline__ void wg_fence() { asm volatile("wgmma.fence.sync.aligned;" ::: "memory"); }
__device__ __forceinline__ void wg_commit() { asm volatile("wgmma.commit_group.sync.aligned;" ::: "memory"); }
template <int N> __device__ __forceinline__ void wg_wait() { asm volatile("wgmma.wait_group.sync.aligned %0;" ::"n"(N) : "memory"); }
__device__ __forceinline__ void bar_sync(int id, int n) { asm volatile("bar.sync %0, %1;" ::"r"(id), "r"(n) : "memory"); }
__device__ __forceinline__ void bar_arrive(int id, int n) { asm volatile("bar.arrive %0, %1;" ::"r"(id), "r"(n) : "memory"); }

constexpr uint32_t DESC_HI_128 = (1024 >> 4) | (1u << 30);
constexpr uint32_t DESC_HI_64 = (512 >> 4) | (2u << 30);
constexpr uint32_t DESC_LBO = (8192 >> 4) << 16;
__device__ __forceinline__ uint64_t make_desc(uint32_t lo, uint32_t hi) { return ((uint64_t)hi << 32) | lo; }

#define R8(a, o) "+f"(a[o]), "+f"(a[o + 1]), "+f"(a[o + 2]), "+f"(a[o + 3]), "+f"(a[o + 4]), "+f"(a[o + 5]), "+f"(a[o + 6]), "+f"(a[o + 7])

template <int ND>
__device__ __forceinline__ void wgmma_n64(float (&d)[ND], const uint32_t (&a)[4], uint64_t desc, int acc) {
    asm volatile(
        "{\n.reg .pred p;\nsetp.ne.b32 p, %37, 0;\n"
        "wgmma.mma_async.sync.aligned.m64n64k16.f32.bf16.bf16 "
        "{%0,%1,%2,%3,%4,%5,%6,%7,%8,%9,%10,%11,%12,%13,%14,%15,%16,%17,%18,%19,%20,%21,%22,%23,%24,%25,%26,%27,%28,%29,%30,%31},"
        "{%32,%33,%34,%35}, %36, p, 1, 1, 1;\n}"
        : R8(d, 0), R8(d, 8), R8(d, 16), R8(d, 24)
        : "r"(a[0]), "r"(a[1]), "r"(a[2]), "r"(a[3]), "l"(desc), "r"(acc));
}
__device__ __forceinline__ void wgmma_n128(float (&d)[64], const uint32_t (&a)[4], uint64_t desc, int acc) {
    asm volatile(
        "{\n.reg .pred p;\nsetp.ne.b32 p, %69, 0;\n"
        "wgmma.mma_async.sync.aligned.m64n128k16.f32.bf16.bf16 "
        "{%0,%1,%2,%3,%4,%5,%6,%7,%8,%9,%10,%11,%12,%13,%14,%15,%16,%17,%18,%19,%20,%21,%22,%23,%24,%25,%26,%27,%28,%29,%30,%31,"
        "%32,%33,%34,%35,%36,%37,%38,%39,%40,%41,%42,%43,%44,%45,%46,%47,%48,%49,%50,%51,%52,%53,%54,%55,%56,%57,%58,%59,%60,%61,%62,%63},"
        "{%64,%65,%66,%67}, %68, p, 1, 1, 1;\n}"
        : R8(d, 0), R8(d, 8), R8(d, 16), R8(d, 24), R8(d, 32), R8(d, 40), R8(d, 48), R8(d, 56)
        : "r"(a[0]), "r"(a[1]), "r"(a[2]), "r"(a[3]), "l"(desc), "r"(acc));
}
__device__ __forceinline__ void wgmma_n128_ss(float (&d)[64], uint64_t da, uint64_t db, int acc) {
    asm volatile(
        "{\n.reg .pred p;\nsetp.ne.b32 p, %66, 0;\n"
        "wgmma.mma_async.sync.aligned.m64n128k16.f32.bf16.bf16 "
        "{%0,%1,%2,%3,%4,%5,%6,%7,%8,%9,%10,%11,%12,%13,%14,%15,%16,%17,%18,%19,%20,%21,%22,%23,%24,%25,%26,%27,%28,%29,%30,%31,"
        "%32,%33,%34,%35,%36,%37,%38,%39,%40,%41,%42,%43,%44,%45,%46,%47,%48,%49,%50,%51,%52,%53,%54,%55,%56,%57,%58,%59,%60,%61,%62,%63},"
        "%64, %65, p, 1, 1, 0, 1;\n}"
        : R8(d, 0), R8(d, 8), R8(d, 16), R8(d, 24), R8(d, 32), R8(d, 40), R8(d, 48), R8(d, 56)
        : "l"(da), "l"(db), "r"(acc));
}
template <int N> __device__ __forceinline__ void fence_regs(float (&d)[N]) {
#pragma unroll
    for (int k = 0; k < N; k++) asm volatile("" : "+f"(d[k])::"memory");
}

struct Ctx {
    uint32_t sm;
    uint32_t bars;
    int lane;
    uint32_t zero;
};

template <int S, int T0, int KSTEP, uint32_t HI, int ND>
__device__ __forceinline__ void stage_n64(const Ctx& c, float (&acc)[ND], const uint32_t (&a)[32][4]) {
    mbar_wait(c.bars + B_FULL + (S & 7) * 8, (S >> 3) & 1);
    wg_fence();
    constexpr uint32_t lo = ((SMD + (S & 7) * STAGE_BYTES) >> 4) | DESC_LBO;
#pragma unroll
    for (int k = 0; k < 8; k++) wgmma_n64(acc, a[T0 + k], make_desc(lo + k * (KSTEP >> 4), HI), (T0 | k) != 0);
    wg_commit();
}
template <int S> __device__ __forceinline__ void release(const Ctx& c) {
    if (c.lane == 0) mbar_arrive(c.bars + B_EMPTY + (S & 7) * 8);
}
__device__ __forceinline__ void centre(uint32_t (&f)[4], uint32_t nm0, uint32_t nm1) {
    f[0] = badd2(f[0], nm0); f[2] = badd2(f[2], nm0);
    f[1] = badd2(f[1], nm1); f[3] = badd2(f[3], nm1);
}

__device__ __forceinline__ void qk_block(float (&s)[8], const uint32_t (&q)[4], uint32_t ks, int t, bool p0, bool p1) {
    const uint4 kf = lds128(ks + t * 512);
    mma16816_z(s[0], s[1], s[2], s[3], q[0], q[1], q[2], q[3], kf.x, kf.y);
    mma16816_z(s[4], s[5], s[6], s[7], q[0], q[1], q[2], q[3], kf.z, kf.w);
    if (t == 0) {
        float d[8];
        const uint4 kd = lds128(ks + 16 * 512);
        mma16816_z(d[0], d[1], d[2], d[3], q[0], q[1], q[2], q[3], kd.x, kd.y);
        mma16816_z(d[4], d[5], d[6], d[7], q[0], q[1], q[2], q[3], kd.z, kd.w);
        s[0] = p0 ? s[0] : d[0];
        s[1] = p1 ? s[1] : d[1];
        s[2] = d[2];
        s[3] = d[3];
        s[6] = p0 ? s[6] : d[6];
        s[7] = p1 ? s[7] : d[7];
    }
}
__device__ __forceinline__ void max_block(int& m0, int& m1, const float (&s)[8]) {
    m0 = __vimax3_s32(__vimax3_s32(m0, __float_as_int(s[0]), __float_as_int(s[1])), __float_as_int(s[4]), __float_as_int(s[5]));
    m1 = __vimax3_s32(__vimax3_s32(m1, __float_as_int(s[2]), __float_as_int(s[3])), __float_as_int(s[6]), __float_as_int(s[7]));
}

__device__ __forceinline__ void attention(const Ctx& c, uint32_t (&q)[4][4], int bi, int w, uint4* go) {
    const int lane = c.lane, g = lane >> 2, cq = lane & 3;
    const bool p0 = 2 * cq > g, p1 = 2 * cq + 1 > g;
    const uint32_t pmask = (p0 ? 0xffffu : 0u) | (p1 ? 0xffff0000u : 0u);
    constexpr float C = 0.25f * 1.4426950408889634f;
    constexpr uint32_t ONES = 0x3f803f80u;
    const uint32_t off = w * 512 + lane * 16;
    float s[16][8];
    int m0 = INT_MIN, m1 = INT_MIN;
    mbar_wait(c.bars + B_K, 0);
    PROF(12);
#pragma unroll
    for (int t = 0; t < 16; t++) {
        qk_block(s[t], q[0], c.sm + SM_K + off, t, p0, p1);
        max_block(m0, m1, s[t]);
    }
#pragma unroll 1
    for (int h = 0; h < 4; h++) {
        m0 = max(m0, __shfl_xor_sync(0xffffffffu, m0, 1));
        m1 = max(m1, __shfl_xor_sync(0xffffffffu, m1, 1));
        m0 = max(m0, __shfl_xor_sync(0xffffffffu, m0, 2));
        m1 = max(m1, __shfl_xor_sync(0xffffffffu, m1, 2));
        float f0 = __int_as_float(m0), f1 = __int_as_float(m1);
        const int nph = 255 - (bi * 128 + w * 16 + g);
        float n0 = (float)max(nph, 0), n1 = (float)max(nph - 8, 0);
        if (__any_sync(0xffffffffu, min(m0, m1) <= 0)) {
            const int tmin = 16 - 8 * bi - w;
            if (tmin > 0) {
                if (p0) { s[0][0] = -1e30f; s[0][6] = -1e30f; }
                if (p1) { s[0][1] = -1e30f; s[0][7] = -1e30f; }
                s[0][4] = -1e30f; s[0][5] = -1e30f;
            }
            f0 = -INFINITY; f1 = -INFINITY;
#pragma unroll
            for (int t = 0; t < 16; t++) {
                if (t > 0 && t < tmin) {
#pragma unroll
                    for (int e = 0; e < 8; e++) s[t][e] = -1e30f;
                }
                f0 = fmaxf(f0, fmaxf(fmaxf(s[t][0], s[t][1]), fmaxf(s[t][4], s[t][5])));
                f1 = fmaxf(f1, fmaxf(fmaxf(s[t][2], s[t][3]), fmaxf(s[t][6], s[t][7])));
            }
            f0 = fmaxf(f0, __shfl_xor_sync(0xffffffffu, f0, 1));
            f1 = fmaxf(f1, __shfl_xor_sync(0xffffffffu, f1, 1));
            f0 = fmaxf(f0, __shfl_xor_sync(0xffffffffu, f0, 2));
            f1 = fmaxf(f1, __shfl_xor_sync(0xffffffffu, f1, 2));
            n0 = 0.f; n1 = 0.f;
        }
        float e0 = -f0 * C, e1 = -f1 * C;
        {
            const uint32_t ph = pack_bf16(ex2(fminf(e0, 0.f)), ex2(fminf(e1, 0.f)));
            n0 *= bf_lo(ph); n1 *= bf_hi(ph);
        }
        m0 = INT_MIN; m1 = INT_MIN;
        if (h < 3) mbar_wait(c.bars + B_K + (h + 1) * 8, 0);
        else if (lane == 0) mbar_arrive(c.bars + B_DEAD);
        mbar_wait(c.bars + B_V + h * 8, 0);
        PROF(13 + h);
        const uint32_t vs = c.sm + SM_V + h * 12288 + off;
        const uint32_t ks = h < 3 ? c.sm + SM_K + (h + 1) * 12288 + off : vs;
        float oa[4], ob[4], oc[4], od[4], l[4];
        int d0 = 0, d1 = 0;
        uint32_t pl = 0;
#pragma unroll
        for (int t = 0; t <= 16; t++) {
            uint32_t p[4];
            if (t < 16) {
                if (t >= 3) {
                    if (t & 1) e1 = tie(e1, d1, c.zero);
                    else e0 = tie(e0, d0, c.zero);
                }
                d0 = m0; d1 = m1;
                p[0] = pack_bf16(ex2(fmaf(s[t][0], C, e0)), ex2(fmaf(s[t][1], C, e0)));
                p[1] = pack_bf16(ex2(fmaf(s[t][2], C, e1)), ex2(fmaf(s[t][3], C, e1)));
                p[2] = pack_bf16(ex2(fmaf(s[t][4], C, e0)), ex2(fmaf(s[t][5], C, e0)));
                p[3] = pack_bf16(ex2(fmaf(s[t][6], C, e1)), ex2(fmaf(s[t][7], C, e1)));
                const uint4 vf = lds128(vs + t * 512);
                if (t == 0) {
                    const uint4 vd = lds128(vs + 16 * 512);
                    mma16816_z(oa[0], oa[1], oa[2], oa[3], p[0] & pmask, 0u, p[2], p[3] & pmask, vf.x, vf.y);
                    mma16816_z(ob[0], ob[1], ob[2], ob[3], p[0] & pmask, 0u, p[2], p[3] & pmask, vf.z, vf.w);
                    mma16816_z(oc[0], oc[1], oc[2], oc[3], p[0] & ~pmask, p[1], 0u, p[3] & ~pmask, vd.x, vd.y);
                    mma16816_z(od[0], od[1], od[2], od[3], p[0] & ~pmask, p[1], 0u, p[3] & ~pmask, vd.z, vd.w);
                    mma16816_z(l[0], l[1], l[2], l[3], p[0], p[1], p[2], p[3], ONES, ONES);
                } else {
                    mma16816(oa[0], oa[1], oa[2], oa[3], p[0], p[1], p[2], p[3], vf.x, vf.y);
                    mma16816(ob[0], ob[1], ob[2], ob[3], p[0], p[1], p[2], p[3], vf.z, vf.w);
                    mma16816(l[0], l[1], l[2], l[3], p[0], p[1], p[2], p[3], ONES, ONES);
                }
            }
            if (t >= 1) {
                qk_block(s[t - 1], q[1], tie(ks, pl, c.zero), t - 1, p0, p1);
                max_block(m0, m1, s[t - 1]);
            }
            if (t < 16) pl = p[3];
        }
        const float i0 = rcp(l[0] - n0), i1 = rcp(l[2] - n1);
        st_ll(go + h * 1024, nz(pack_bf16((oa[0] + oc[0]) * i0, (oa[1] + oc[1]) * i0)),
              nz(pack_bf16((oa[2] + oc[2]) * i1, (oa[3] + oc[3]) * i1)), nz(pack_bf16((ob[0] + od[0]) * i0, (ob[1] + od[1]) * i0)),
              nz(pack_bf16((ob[2] + od[2]) * i1, (ob[3] + od[3]) * i1)));
#pragma unroll
        for (int e = 0; e < 4; e++) { q[1][e] = q[2][e]; q[2][e] = q[3][e]; }
        if (SKEW == 2 && h == 0 && w < 4) bar_arrive(2, 256);
    }
}

__device__ __forceinline__ void fill_a(uint32_t sm, uint32_t bars, int bi, int bj, int q, int wg) {
    const int sl = q < 6 ? q : q < 12 ? q - 6 : q - 12;
    const uint32_t bar = bars + B_WG + wg * 128 + W_INA + sl * 8, dst = sm + SM_K + wg * 49152 + sl * 8192;
    mbar_expect(bar, 8192);
    if (q < 12) {
        const int ck = q / 3 - 1, r = q - 3 * ck - 2;
        bulk_g2s(dst, g_hff + ((bi * 8 + ((bj + 2 * r) & 7)) * 8 + wg * 4 + ck) * 512, 8192, bar);
    } else {
        bulk_g2s(dst, g_hff + ((bi * 8 + ((bj + 4 * sl) & 7)) * 8 + wg * 4 + 3) * 512, 4096, bar);
        bulk_g2s(dst + 4096, g_hff + ((bi * 8 + ((bj + 4 * sl + 2) & 7)) * 8 + wg * 4 + 3) * 512, 4096, bar);
    }
}

__global__ void __cluster_dims__(2, 1, 1) __launch_bounds__(384, 1) fused_block_kernel(const __grid_constant__ Params P) {
    const uint32_t sm = smem_u32(smem_raw);
    if ((sm & 0x3ffffu) != SMD) return;
    const uint32_t bars = sm + SM_BAR;
    const int tid = threadIdx.x, lane = tid & 31;
    const int warp = __shfl_sync(0xffffffffu, tid >> 5, 0);
    const int bi = blockIdx.x >> 3, bj = blockIdx.x & 7;

    if (lane == 0) {
        if (warp < 8) {
            const uint32_t nsrc = bi > 1 ? 2 : bi;
            mbar_init(bars + B_FULL + warp * 8, 1);
            mbar_init(bars + B_EMPTY + warp * 8, 8);
            mbar_init(bars + B_K + warp * 8, 8 + nsrc);
            mbar_init(bars + B_XCH + warp * 8, 1);
            mbar_expect(bars + B_XCH + warp * 8, 2048);
        } else if (warp == 8) {
#pragma unroll
            for (int k = 0; k < 8; k++) mbar_init(bars + B_X + k * 8, 1);
        } else if (warp == 9) {
            mbar_init(bars + B_XFREE, 8);
            mbar_init(bars + B_DEAD, 8);
            mbar_init(bars + B_DEAD + 8, 8);
#pragma unroll
            for (int k = 0; k < 4; k++) mbar_init(bars + B_PUB + k * 8, 8);
            mbar_init(bars + B_S5, 1);
            mbar_init(bars + B_LVL, 1);
            mbar_init(bars + B_LVL + 8, 1);
        } else {
#pragma unroll
            for (int k = 0; k < 14; k++) mbar_init(bars + B_WG + (warp - 10) * 128 + k * 8, k < 12 ? 1 : 4);
        }
        asm volatile("fence.mbarrier_init.release.cluster;" ::: "memory");
    }
    __syncwarp();
    if (warp == 8) {
        bar_arrive(0, 384);
    } else {
        bar_arrive(1, 384);
        bar_sync(0, 384);
    }

    if (warp >= 8) {
        asm volatile("setmaxnreg.dec.sync.aligned.u32 40;");
        if (warp == 8) {
            if (lane == 0) {
#pragma unroll 1
                for (int kb = 0; kb < 8; kb++) {
                    mbar_expect(bars + B_X + kb * 8, 16384);
                    tma2d(sm + (kb < 6 ? SM_K + kb * 16384 : kb * STAGE_BYTES), &P.xm, bars + B_X + kb * 8, kb * 64, bi * 128);
                }
            }
            __syncwarp();
            bar_sync(1, 384);
            if (lane == 0) {
                int s = 0;
                auto acquire = [&]() -> uint32_t {
                    const int slot = s & 7;
                    if (s >= 8) mbar_wait(bars + B_EMPTY + slot * 8, ((s >> 3) - 1) & 1);
                    else if (s == 6) mbar_wait(bars + B_XFREE, 0);
                    if (s == 19) mbar_wait(bars + B_EMPTY + 4 * 8, 1);
                    mbar_expect(bars + B_FULL + slot * 8, 16384);
                    s++;
                    return slot;
                };
#pragma unroll 1
                for (int p = 0; p < 12; p++) {
                    const int col = (p < 4 ? 512 : p < 8 ? 1024 : 0) + 64 * bj;
                    const uint32_t slot = acquire();
                    tma2d(sm + slot * STAGE_BYTES, &P.qkv, bars + B_FULL + slot * 8, col, (p & 3) * 128);
                }
#pragma unroll 1
                for (int q = 0; q < 4; q++) {
                    const uint32_t slot = acquire();
                    tma2d(sm + slot * STAGE_BYTES, &P.wo, bars + B_FULL + slot * 8, 64 * bj, q * 128);
                }
                {
                    const uint32_t slot = acquire();
                    tma2d(sm + slot * STAGE_BYTES, &P.xm, bars + B_FULL + slot * 8, 64 * bj, bi * 128);
                }
#pragma unroll 1
                for (int q = 0; q < 24; q++) {
                    const uint32_t slot = acquire();
                    tma2d(sm + slot * STAGE_BYTES, &P.wg, bars + B_FULL + slot * 8, 224 * bj + 64 * (q >> 3), (q & 7) * 64);
                    tma2d(sm + slot * STAGE_BYTES + 8192, &P.wu, bars + B_FULL + slot * 8, 224 * bj + 64 * (q >> 3), (q & 7) * 64);
                }
#pragma unroll 1
                for (int q = 0; q < 4; q++) {
                    const uint32_t slot = acquire();
                    tma2d(sm + slot * STAGE_BYTES, &P.wg2, bars + B_FULL + slot * 8, 224 * bj + 192, q * 128);
                    tma2d(sm + slot * STAGE_BYTES + 8192, &P.wu2, bars + B_FULL + slot * 8, 224 * bj + 192, q * 128);
                }
                const int c0 = 64 * bj, c1 = 64 * (bj ^ 1);
#pragma unroll 1
                for (int q = 0; q < 16; q++) {
                    if (q >= 8) {
                        mbar_wait(bars + B_EMPTY + ((37 + q) & 7) * 8, ((37 + q) >> 3) & 1);
                        if (q == 8) mbar_wait(bars + B_WG + W_INA + 24, 0);
                        if (q == 10 || q == 14) mbar_wait(bars + B_LVL + (q == 14) * 8, 0);
                        fill_a(sm, bars, bi, bj, q - 2, 0);
                        fill_a(sm, bars, bi, bj, q - 2, 1);
                    }
                    if (q < 12) {
                        const int ck = q < 3 ? q : q / 3 - 1, r = q < 3 ? 0 : q - 3 * ck - 2;
                        const int row = 224 * ((bj + 2 * r) & 7) + 64 * ck;
                        const uint32_t slot = acquire();
                        tma2d(sm + slot * STAGE_BYTES, &P.wd, bars + B_FULL + slot * 8, c0, row);
                        tma2d(sm + slot * STAGE_BYTES + 8192, &P.wd, bars + B_FULL + slot * 8, c1, row);
                    } else if (q < 14) {
                        const uint32_t slot = acquire();
                        for (int hh = 0; hh < 2; hh++) {
                            const int row = 224 * ((bj + 4 * (q - 12) + 2 * hh) & 7) + 192;
                            tma2d(sm + slot * STAGE_BYTES + hh * 4096, &P.wd2, bars + B_FULL + slot * 8, c0, row);
                            tma2d(sm + slot * STAGE_BYTES + 8192 + hh * 4096, &P.wd2, bars + B_FULL + slot * 8, c1, row);
                        }
                    }
                }
            }
        } else {
            const unsigned ep = *(volatile unsigned*)&g_epoch[blockIdx.x * 32];
            if (warp == 9) {
                if (lane == 0) {
                    prefetch_tmap(&P.qkv); prefetch_tmap(&P.wo); prefetch_tmap(&P.wg); prefetch_tmap(&P.wu); prefetch_tmap(&P.wg2);
                    prefetch_tmap(&P.wu2); prefetch_tmap(&P.wd); prefetch_tmap(&P.wd2); prefetch_tmap(&P.om);
                }
                mbar_wait(bars + B_V + 24, 0);
                constexpr int PER = sizeof(Scratch) / 16 / NCTA;
                uint4* p = (uint4*)&g_scr[(ep & 1) ^ 1] + blockIdx.x * PER + lane;
#pragma unroll 2
                for (int k = 0; k < PER / 32; k++) stg128(p + k * 32, 0, 0, 0, 0);
                if (lane == 0) {
#pragma unroll 1
                    for (int u = 0; u < 4; u++) {
                        mbar_wait(bars + B_PUB + u * 8, 0);
                        const uint32_t src = sm + SM_K + (u < 3 ? u : 5) * 8192, bytes = u < 3 ? 8192 : 4096;
                        bulk_s2g(g_hff + (blockIdx.x * 8 + u) * 512, src, bytes);
                        bulk_s2g(g_hff + (blockIdx.x * 8 + 4 + u) * 512, src + 49152, bytes);
                        asm volatile("cp.async.bulk.commit_group;" ::: "memory");
                        if (u == 3) {
                            asm volatile("cp.async.bulk.wait_group.read 0;" ::: "memory");
                            mbar_arrive(bars + B_S5);
                        }
                        if (u > 0) {
                            asm volatile("cp.async.bulk.wait_group 0;" ::: "memory");
                            flag_set(&g_flagF[blockIdx.x * 32], 4 * ep + u);
                        }
                    }
                }
            } else {
                const int d = warp - 9;
                if (bi >= d) {
                    const int src = blockIdx.x - 8 * d;
                    const uint4* skv = g_scr[ep & 1].kv + src * 2048 + lane;
                    const uint32_t dkv = sm + SM_K + (2 - d) * 4096 + lane * 16;
                    mbar_wait(bars + B_XFREE, 0);
#pragma unroll 1
                    for (int r = 0; r < 5; r++) {
                        const int u0 = (0x73240 >> (4 * r)) & 7, u1 = (0x76541 >> (4 * r)) & 7;
#pragma unroll 1
                        for (int it = 0; it < SPIN_LIMIT; it++) {
#pragma unroll
                            for (int b = 0; b < 8; b++) cp_async16(dkv + u0 * 12288 + b * 512, skv + u0 * 256 + b * 32);
                            if (u1 != u0) {
#pragma unroll
                                for (int b = 0; b < 8; b++) cp_async16(dkv + u1 * 12288 + b * 512, skv + u1 * 256 + b * 32);
                            }
                            asm volatile("cp.async.wait_all;" ::: "memory");
                            uint32_t m = 0xffffffffu;
#pragma unroll 4
                            for (int b = 0; b < 8; b++) {
                                m = umin4(m, lds128(dkv + u0 * 12288 + b * 512));
                                m = umin4(m, lds128(dkv + u1 * 12288 + b * 512));
                            }
                            if (!warp_bad(m)) break;
                        }
                        if (lane == 0) mbar_arrive(bars + B_K + u0 * 8);
                        if (lane == 1 && u1 != u0) mbar_arrive(bars + B_K + u1 * 8);
                    }
                }
                const int wg = d - 1;
                const uint32_t wb = bars + B_WG + wg * 128, ws = sm + SM_K + wg * 49152;
                const Scratch* scr = &g_scr[ep & 1];
                if (lane == 0) {
                    mbar_wait(bars + B_DEAD, 0);
#pragma unroll 1
                    for (int u = 0; u < 3; u++) {
                        if (u == 2) __nanosleep(500);
                        mbar_expect(wb + W_INO + u * 8, 16384);
                        bulk_g2s(wg == 1 && u == 2 ? sm + 3 * STAGE_BYTES : ws + u * 16384, scr->o + ((bi * 2 + wg) * 4 + u) * 1024, 16384,
                                 wb + W_INO + u * 8);
                    }
                }
                __syncwarp();
                {
                    const uint32_t* st = (const uint32_t*)(scr->stat + (bi * 8 + wg * 4) * 64 + lane * 2);
#pragma unroll 1
                    for (int it = 0; it < SPIN_LIMIT; it++) {
                        uint32_t m = 0xffffffffu;
#pragma unroll
                        for (int b = 0; b < 4; b++) m = min(m, ld_ll1(st + b * 256));
                        if (!warp_bad(m)) break;
                    }
                }
                if (lane == 0) {
                    mbar_wait(bars + B_DEAD + 8, 0);
                    mbar_wait(wb + W_ODEAD, 0);
                    if (HORDER && wg == 1) mbar_wait(bars + B_WG + W_INH + (HORDER - 1) * 8, 0);
#pragma unroll 1
                    for (int u = 0; u < 3; u++) {
                        mbar_expect(wb + W_INH + u * 8, 16384);
                        bulk_g2s(ws + u * 16384, scr->h + ((bi * 2 + wg) * 4 + u + 1) * 1024, 16384, wb + W_INH + u * 8);
                    }
                    mbar_wait(wb + W_HDEAD, 0);
                }
                __syncwarp();
                const unsigned* fl = &g_flagF[(bi * 8 + ((bj + 2 * lane) & 7)) * 32];
#pragma unroll 1
                for (int lvl = 1; lvl < (wg == 0 ? 4 : 2); lvl++) {
#pragma unroll 1
                    for (int it = 0; it < 4 * SPIN_LIMIT; it++) {
                        const bool ok = lane >= 4 || (int)(ld_acquire(fl) - 4 * ep) >= lvl;
                        if (__all_sync(0xffffffffu, ok)) break;
                        __nanosleep(100);
                    }
                    if (lane == 0) {
                        if (lvl == 1) {
                            fill_a(sm, bars, bi, bj, 3, wg);
                            fill_a(sm, bars, bi, bj, 4, wg);
                        } else {
                            mbar_arrive(bars + B_LVL + (lvl - 2) * 8);
                        }
                    }
                    __syncwarp();
                }
                if (wg == 1 && lane == 0) {
                    mbar_wait(bars + B_S5, 0);
                    fill_a(sm, bars, bi, bj, 5, 0);
                    fill_a(sm, bars, bi, bj, 5, 1);
                }
            }
        }
    } else {
        asm volatile("setmaxnreg.inc.sync.aligned.u32 232;");
        const int w = warp, wg = warp >> 2, g = lane >> 2, cq = lane & 3;
        const Ctx c{sm, bars, lane, P.zero};
        const unsigned epoch = *(volatile unsigned*)&g_epoch[blockIdx.x * 32];
        Scratch* const scr = &g_scr[epoch & 1];
        uint32_t a[32][4];
        float rs0, rs1;
        uint32_t qf[4][4];
        const uint32_t lsm = (w * 16 + (lane & 15)) * 128;
        {
            constexpr uint32_t ONES = 0x3f803f80u;
            float sa[2][4], qa[4], qb[4];
#pragma unroll
            for (int kb = 0; kb < 8; kb++) {
                mbar_wait(bars + B_X + kb * 8, 0);
                const uint32_t base = sm + (kb < 6 ? SM_K + kb * 16384 : kb * STAGE_BYTES) + lsm;
#pragma unroll
                for (int u = 0; u < 4; u++) ldsm4(a[kb * 4 + u], base + (((2 * u + (lane >> 4)) ^ (lane & 7)) << 4));
#pragma unroll
                for (int u = 0; u < 4; u++) {
                    const int t = kb * 4 + u;
                    float* sp = sa[u & 1];
                    if (t < 2) mma16816_z(sp[0], sp[1], sp[2], sp[3], a[t][0], a[t][1], a[t][2], a[t][3], ONES, ONES);
                    else mma16816(sp[0], sp[1], sp[2], sp[3], a[t][0], a[t][1], a[t][2], a[t][3], ONES, ONES);
                }
#pragma unroll
                for (int u = 0; u < 4; u++) {
                    const int t = kb * 4 + u;
                    if (t == 0) {
                        mma16816_z(qa[0], qa[1], qa[2], qa[3], a[t][0], a[t][1], a[t][2], a[t][3], a[t][0], a[t][2]);
                        mma16816_z(qb[0], qb[1], qb[2], qb[3], a[t][0], a[t][1], a[t][2], a[t][3], a[t][1], a[t][3]);
                    } else {
                        mma16816(qa[0], qa[1], qa[2], qa[3], a[t][0], a[t][1], a[t][2], a[t][3], a[t][0], a[t][2]);
                        mma16816(qb[0], qb[1], qb[2], qb[3], a[t][0], a[t][1], a[t][2], a[t][3], a[t][1], a[t][3]);
                    }
                }
            }
            const float m0 = (sa[0][0] + sa[1][0]) * (1.f / DM), m1 = (sa[0][2] + sa[1][2]) * (1.f / DM);
            __syncwarp();
            if (lane == 0) mbar_arrive(bars + B_XFREE);
            PROF(26);
            const uint32_t nm0 = pack_bf16(-m0, -m0), nm1 = pack_bf16(-m1, -m1);
            float accA[32], accB[32];
            uint4* const gkv = scr->kv + blockIdx.x * 2048 + w * 32 + lane;
#pragma unroll
            for (int t = 0; t < 8; t++) centre(a[t], nm0, nm1);
            stage_n64<0, 0, 2048, DESC_HI_128>(c, accA, a);
#pragma unroll
            for (int t = 8; t < 16; t++) centre(a[t], nm0, nm1);
            stage_n64<1, 8, 2048, DESC_HI_128>(c, accA, a);
#pragma unroll
            for (int t = 16; t < 32; t++) centre(a[t], nm0, nm1);
            {
                const int dl = (lane & ~3) | (g >> 1);
                const float q0 = __shfl_sync(0xffffffffu, (g & 1) ? qa[1] : qa[0], dl);
                const float q1 = __shfl_sync(0xffffffffu, (g & 1) ? qb[3] : qb[2], dl);
                rs0 = rsqrtf(fmaxf(q0 * (1.f / DM) - m0 * m0, 0.f) + 1e-5f);
                rs1 = rsqrtf(fmaxf(q1 * (1.f / DM) - m1 * m1, 0.f) + 1e-5f);
            }
            wg_wait<1>(); release<0>(c);
            stage_n64<2, 16, 2048, DESC_HI_128>(c, accA, a);
            wg_wait<1>(); release<1>(c);
            stage_n64<3, 24, 2048, DESC_HI_128>(c, accA, a);
            wg_wait<1>(); release<2>(c);
            stage_n64<4, 0, 2048, DESC_HI_128>(c, accB, a);
            wg_wait<1>(); release<3>(c);
            fence_regs(accA);
            mbar_wait(bars + B_XFREE, 0);
#pragma unroll
            for (int h = 0; h < 4; h++) {
                const uint32_t d01 = nz(pack_bf16(accA[h * 8 + 0] * rs0, accA[h * 8 + 1] * rs0));
                const uint32_t d23 = nz(pack_bf16(accA[h * 8 + 2] * rs1, accA[h * 8 + 3] * rs1));
                const uint32_t d45 = nz(pack_bf16(accA[h * 8 + 4] * rs0, accA[h * 8 + 5] * rs0));
                const uint32_t d67 = nz(pack_bf16(accA[h * 8 + 6] * rs1, accA[h * 8 + 7] * rs1));
                st_ll(gkv + h * 256, d01, d45, d23, d67);
                sts128(sm + SM_K + h * 12288 + (16 + w) * 512 + lane * 16, d01, d45, d23, d67);
            }
            if (bi < 2) {
                for (int b = w; b < (2 - bi) * 8; b += 8)
#pragma unroll
                    for (int h = 0; h < 4; h++) {
                        sts128(sm + SM_K + h * 12288 + b * 512 + lane * 16, 0, 0, 0, 0);
                        sts128(sm + SM_V + h * 12288 + b * 512 + lane * 16, 0, 0, 0, 0);
                    }
            }
            __syncwarp();
            if (lane < 4) mbar_arrive(bars + B_K + lane * 8);
            stage_n64<5, 8, 2048, DESC_HI_128>(c, accB, a);
            wg_wait<1>(); release<4>(c);
            stage_n64<6, 16, 2048, DESC_HI_128>(c, accB, a);
            wg_wait<1>(); release<5>(c);
            stage_n64<7, 24, 2048, DESC_HI_128>(c, accB, a);
            wg_wait<1>(); release<6>(c);
            auto epiV = [&]() {
                fence_regs(accB);
                release<7>(c);
#pragma unroll
                for (int h = 0; h < 4; h++) {
                    const uint32_t d01 = nz(movtrans(pack_bf16(accB[h * 8 + 0] * rs0, accB[h * 8 + 1] * rs0)));
                    const uint32_t d23 = nz(movtrans(pack_bf16(accB[h * 8 + 2] * rs1, accB[h * 8 + 3] * rs1)));
                    const uint32_t d45 = nz(movtrans(pack_bf16(accB[h * 8 + 4] * rs0, accB[h * 8 + 5] * rs0)));
                    const uint32_t d67 = nz(movtrans(pack_bf16(accB[h * 8 + 6] * rs1, accB[h * 8 + 7] * rs1)));
                    st_ll(gkv + (4 + h) * 256, d01, d23, d45, d67);
                    sts128(sm + SM_V + h * 12288 + (16 + w) * 512 + lane * 16, d01, d23, d45, d67);
                }
                __syncwarp();
                if (lane < 4) mbar_arrive(bars + B_V + lane * 8);
            };
            if (SKEW >= 1 && wg == 1) {
                wg_wait<0>();
                epiV();
                bar_sync(3, 256);
                stage_n64<8, 0, 2048, DESC_HI_128>(c, accA, a);
            } else {
                stage_n64<8, 0, 2048, DESC_HI_128>(c, accA, a);
                wg_wait<1>();
                epiV();
            }
            stage_n64<9, 8, 2048, DESC_HI_128>(c, accA, a);
            wg_wait<1>(); release<8>(c);
            stage_n64<10, 16, 2048, DESC_HI_128>(c, accA, a);
            wg_wait<1>(); release<9>(c);
            stage_n64<11, 24, 2048, DESC_HI_128>(c, accA, a);
            if (SKEW >= 1 && wg == 0) bar_arrive(3, 256);
            wg_wait<1>(); release<10>(c);
            wg_wait<0>(); release<11>(c);
            fence_regs(accA);
#pragma unroll
            for (int h = 0; h < 4; h++) {
                qf[h][0] = pack_bf16(accA[h * 8 + 0] * rs0, accA[h * 8 + 1] * rs0);
                qf[h][1] = pack_bf16(accA[h * 8 + 2] * rs1, accA[h * 8 + 3] * rs1);
                qf[h][2] = pack_bf16(accA[h * 8 + 4] * rs0, accA[h * 8 + 5] * rs0);
                qf[h][3] = pack_bf16(accA[h * 8 + 6] * rs1, accA[h * 8 + 7] * rs1);
            }
        }
        if (SKEW == 2 && wg == 1) bar_sync(2, 256);
        PROF(3);
        const int rec0 = ((bi * 2 + wg) * 16 + (w & 3)) * 256 + lane;
        attention(c, qf, bi, w, scr->o + rec0 + bj * 32);
        PROF(4);
        const uint32_t wb = bars + B_WG + wg * 128, ws = sm + SM_K + wg * 49152;
        {
            const uint4* src = scr->o + rec0;
            __syncwarp();
            if (lane == 0) mbar_arrive(bars + B_DEAD + 8);
            float acc[32];
#pragma unroll
            for (int q = 0; q < 4; q++) mbar_wait(bars + B_FULL + (4 + q) * 8, 1);
            constexpr uint32_t lo = ((SMD + 4 * STAGE_BYTES) >> 4) | DESC_LBO;
            const uint32_t os = ws + (w & 3) * 4096 + lane * 16;
            const uint32_t os2 = wg == 1 ? sm + 3 * STAGE_BYTES + (w & 3) * 4096 + lane * 16 : os + 32768;
            auto mma8 = [&](int u) {
                wg_fence();
#pragma unroll
                for (int k = 0; k < 8; k++) wgmma_n64(acc, a[u * 8 + k], make_desc(lo + (4 * k + u) * 128, DESC_HI_128), (u | k) != 0);
                wg_commit();
            };
            mbar_wait(wb + W_INO, 0);
#pragma unroll
            for (int k = 0; k < 8; k++) lds4(a[k], os + k * 512);
            mbar_wait(wb + W_INO + 8, 0);
#pragma unroll
            for (int k = 0; k < 8; k++) lds4(a[8 + k], os + 16384 + k * 512);
            validate8<0, 0>(a, src);
            PROF(5);
            mma8(0);
            mbar_wait(wb + W_INO + 16, 0);
#pragma unroll
            for (int k = 0; k < 8; k++) lds4(a[16 + k], os2 + k * 512);
            validate8<8, 1>(a, src + 1024);
            validate8<16, 2>(a, src + 2048);
            if (lane == 0) mbar_arrive(wb + W_ODEAD);
            PROF(0);
#pragma unroll
            for (int k = 0; k < 8; k++) ld_ll4(a[24 + k], src + 3072 + k * 32);
            mma8(1);
            mma8(2);
            PROF(24);
            validate8<24, 3>(a, src + 3072);
            PROF(27);
            mma8(3);
            uint32_t xr[4][4];
            mbar_wait(bars + B_FULL, 0);
#pragma unroll
            for (int u = 0; u < 4; u++) ldsm4(xr[u], sm + lsm + (((2 * u + (lane >> 4)) ^ (lane & 7)) << 4));
            const uint32_t* xres = &xr[0][0];
            wg_wait<0>();
            fence_regs(acc);
            __syncwarp();
            if (lane < 5) mbar_arrive(bars + B_EMPTY + ((4 + lane) & 7) * 8);
            PROF(6);
            float s0 = 0.f, s1 = 0.f, q0 = 0.f, q1 = 0.f;
            uint32_t hp[16];
#pragma unroll
            for (int b = 0; b < 8; b++) {
                hp[2 * b] = nz(pack_bf16(acc[4 * b + 0] + bf_lo(xres[2 * b]), acc[4 * b + 1] + bf_hi(xres[2 * b])));
                hp[2 * b + 1] = nz(pack_bf16(acc[4 * b + 2] + bf_lo(xres[2 * b + 1]), acc[4 * b + 3] + bf_hi(xres[2 * b + 1])));
            }
            uint4* dst = scr->h + rec0 + (bj >> 1) * 1024 + (bj & 1) * 128;
#pragma unroll
            for (int k = 0; k < 4; k++) st_ll(dst + k * 32, hp[4 * k], hp[4 * k + 1], hp[4 * k + 2], hp[4 * k + 3]);
            asm volatile("" ::: "memory");
#pragma unroll
            for (int b = 0; b < 8; b++) {
                float v;
                v = bf_lo(hp[2 * b]); s0 += v; q0 = fmaf(v, v, q0);
                v = bf_hi(hp[2 * b]); s0 += v; q0 = fmaf(v, v, q0);
                v = bf_lo(hp[2 * b + 1]); s1 += v; q1 = fmaf(v, v, q1);
                v = bf_hi(hp[2 * b + 1]); s1 += v; q1 = fmaf(v, v, q1);
            }
#pragma unroll
            for (int m = 1; m <= 2; m <<= 1) {
                s0 += __shfl_xor_sync(0xffffffffu, s0, m); q0 += __shfl_xor_sync(0xffffffffu, q0, m);
                s1 += __shfl_xor_sync(0xffffffffu, s1, m); q1 += __shfl_xor_sync(0xffffffffu, q1, m);
            }
            if (cq == 0)
                st_ll(scr->stat + ((bi * 8 + w) * 8 + bj) * 8 + g, nz(__float_as_uint(s0)), nz(__float_as_uint(q0)),
                      nz(__float_as_uint(s1)), nz(__float_as_uint(q1)));
            PROF(17);
        }
        float r20, r21;
        uint32_t nm0, nm1;
        const uint4* hsrc = scr->h + rec0;
        {
            const uint4* st = scr->stat + ((bi * 8 + w) * 8 + cq) * 8 + g;
            uint4 sa, sb;
#pragma unroll 1
            for (int it = 0; it < SPIN_LIMIT; it++) {
                sa = ld_ll(st);
                sb = ld_ll(st + 32);
                if (!warp_bad(umin4(umin4(0xffffffffu, sa), sb))) break;
            }
            PROF(7);
#pragma unroll
            for (int t = 0; t < 8; t++) ld_ll4(a[t], hsrc + t * 32);
            float s0 = __uint_as_float(sa.x) + __uint_as_float(sb.x), q0 = __uint_as_float(sa.y) + __uint_as_float(sb.y);
            float s1 = __uint_as_float(sa.z) + __uint_as_float(sb.z), q1 = __uint_as_float(sa.w) + __uint_as_float(sb.w);
#pragma unroll
            for (int m = 1; m <= 2; m <<= 1) {
                s0 += __shfl_xor_sync(0xffffffffu, s0, m); q0 += __shfl_xor_sync(0xffffffffu, q0, m);
                s1 += __shfl_xor_sync(0xffffffffu, s1, m); q1 += __shfl_xor_sync(0xffffffffu, q1, m);
            }
            const float m0 = s0 * (1.f / DM), m1 = s1 * (1.f / DM);
            r20 = __fdividef(1.f, fmaxf(q0 * (1.f / DM) - m0 * m0, 0.f) + 1e-5f);
            r21 = __fdividef(1.f, fmaxf(q1 * (1.f / DM) - m1 * m1, 0.f) + 1e-5f);
            nm0 = pack_bf16(-m0, -m0); nm1 = pack_bf16(-m1, -m1);
        }
        const uint32_t hff = ws + (w & 3) * 512 + ((lane >> 3) & 1) * 256 + (lane >> 4) * 128 + (lane & 7) * 16;
#pragma unroll 1
        for (int ch = 0; ch < 3; ch++) {
            float acc[64];
#pragma unroll
            for (int q = 0; q < 8; q++) {
                if (ch == 0 && (q & 1) == 0) {
                    if (q > 0) {
                        mbar_wait(wb + W_INH + (q / 2 - 1) * 8, 0);
#pragma unroll
                        for (int k = 0; k < 8; k++) lds4(a[q * 4 + k], ws + (w & 3) * 4096 + lane * 16 + (q / 2 - 1) * 16384 + k * 512);
                    }
                    if (q == 0) validate8<0, 4>(a, hsrc);
                    if (q == 2) validate8<8, 5>(a, hsrc + 1024);
                    if (q == 4) validate8<16, 6>(a, hsrc + 2048);
                    if (q == 6) validate8<24, 7>(a, hsrc + 3072);
#pragma unroll
                    for (int k = 0; k < 8; k++) centre(a[q * 4 + k], nm0, nm1);
                    if (q == 0) PROF(8);
                    if (q == 6 && lane == 0) mbar_arrive(wb + W_HDEAD);
                }
                mbar_wait(bars + B_FULL + ((q + 1) & 7) * 8, (ch + (q == 7)) & 1);
                wg_fence();
                constexpr uint32_t lo0 = (SMD >> 4) | DESC_LBO;
#pragma unroll
                for (int k = 0; k < 4; k++)
                    wgmma_n128(acc, a[q * 4 + k], make_desc(lo0 + ((q + 1) & 7) * 1024 + k * 128, DESC_HI_128), (q | k) != 0);
                wg_commit();
                if (q > 0) {
                    wg_wait<1>();
                    if (lane == 0) mbar_arrive(bars + B_EMPTY + q * 8);
                }
            }
            wg_wait<0>();
            fence_regs(acc);
            if (lane == 0) mbar_arrive(bars + B_EMPTY);
            if (ch == 0) mbar_wait(wb + W_HDEAD, 0);
#pragma unroll
            for (int k = 0; k < 4; k++) {
                uint32_t f[4];
#pragma unroll
                for (int e = 0; e < 4; e++) {
                    const int i0 = k * 8 + e * 2;
                    const float r = (e & 1) ? r21 : r20;
                    f[e] = pack_bf16(fmaxf(acc[i0], 0.f) * r * acc[32 + i0], fmaxf(acc[i0 + 1], 0.f) * r * acc[32 + i0 + 1]);
                }
                stsm4(hff + ch * 8192 + k * 2048, f[0], f[1], f[2], f[3]);
            }
            asm volatile("fence.proxy.async.shared::cta;" ::: "memory");
            __syncwarp();
            if (lane == 0) mbar_arrive(bars + B_PUB + ch * 8);
            PROF(28 + ch);
        }
        uint32_t hres[4][4];
#pragma unroll
        for (int k = 0; k < 4; k++) ld_cg4(hres[k], hsrc + (bj >> 1) * 1024 + (bj & 1) * 128 + k * 32);
        {
            float acc[32];
            stage_n64<41, 0, 1024, DESC_HI_64>(c, acc, a);
            stage_n64<42, 8, 1024, DESC_HI_64>(c, acc, a);
            wg_wait<1>(); release<41>(c);
            stage_n64<43, 16, 1024, DESC_HI_64>(c, acc, a);
            wg_wait<1>(); release<42>(c);
            stage_n64<44, 24, 1024, DESC_HI_64>(c, acc, a);
            wg_wait<1>(); release<43>(c);
            wg_wait<0>(); release<44>(c);
            fence_regs(acc);
#pragma unroll
            for (int k = 0; k < 2; k++) {
                uint32_t f[4];
#pragma unroll
                for (int e = 0; e < 4; e++) {
                    const int i0 = k * 8 + e * 2;
                    const float r = (e & 1) ? r21 : r20;
                    f[e] = pack_bf16(fmaxf(acc[i0], 0.f) * r * acc[16 + i0], fmaxf(acc[i0 + 1], 0.f) * r * acc[16 + i0 + 1]);
                }
                stsm4(hff + 5 * 8192 + k * 2048, f[0], f[1], f[2], f[3]);
            }
            asm volatile("fence.proxy.async.shared::cta;" ::: "memory");
            __syncwarp();
            if (lane == 0) mbar_arrive(bars + B_PUB + 24);
        }
        PROF(9);
        {
            float acc[64];
            mbar_wait(bars + B_PUB + 16, 0);
            const uint32_t alo = ((SMD + SM_K + wg * 49152) >> 4) | ((128 >> 4) << 16);
#pragma unroll 1
            for (int q = 0; q < 14; q++) {
                const int s = 45 + q, slot = s & 7, sl = q < 6 ? q : q < 12 ? q - 6 : q - 12;
                if (q >= 3) mbar_wait(wb + W_INA + sl * 8, q >= 9);
                mbar_wait(bars + B_FULL + slot * 8, (s >> 3) & 1);
                wg_fence();
                const uint32_t lo = ((SMD + slot * STAGE_BYTES) >> 4) | DESC_LBO;
#pragma unroll
                for (int k = 0; k < 4; k++)
                    wgmma_n128_ss(acc, make_desc(alo + sl * 512 + k * 128, 256 >> 4), make_desc(lo + k * 128, DESC_HI_128), (q | k) != 0);
                wg_commit();
                wg_wait<1>();
                if (q > 0 && q <= 8 && lane == 0) mbar_arrive(bars + B_EMPTY + ((s - 1) & 7) * 8);
                if (q == 10) asm volatile("barrier.cluster.arrive.relaxed.aligned;" ::: "memory");
                PROF(32 + q);
            }
            asm volatile("barrier.cluster.wait.acquire.aligned;" ::: "memory");
            wg_wait<0>();
            fence_regs(acc);
            PROF(10);
            const uint32_t peer = (blockIdx.x & 1) ^ 1;
            const uint32_t xch = ws + 2 * 8192 + (w & 3) * 2048 + lane * 16;
            const uint32_t rdst = mapa(xch, peer), rbar = mapa(bars + B_XCH + w * 8, peer);
#pragma unroll
            for (int b = 0; b < 4; b++)
                st_async4(rdst + b * 512, rbar, pack_bf16(acc[32 + 8 * b], acc[33 + 8 * b]), pack_bf16(acc[34 + 8 * b], acc[35 + 8 * b]),
                          pack_bf16(acc[36 + 8 * b], acc[37 + 8 * b]), pack_bf16(acc[38 + 8 * b], acc[39 + 8 * b]));
#pragma unroll
            for (int k = 0; k < 16; k++) {
                acc[2 * k] += bf_lo(hres[k >> 2][k & 3]);
                acc[2 * k + 1] += bf_hi(hres[k >> 2][k & 3]);
            }
            mbar_wait_cluster(bars + B_XCH + w * 8, 0);
            PROF(31);
#pragma unroll
            for (int b = 0; b < 4; b++) {
                const uint4 u = lds128(xch + b * 512);
                stsm4(ws + 3 * 8192 + (w & 3) * 2048 + (lane & 15) * 128 + (((2 * b + (lane >> 4)) ^ (lane & 7)) << 4),
                      pack_bf16(acc[8 * b] + bf_lo(u.x), acc[8 * b + 1] + bf_hi(u.x)),
                      pack_bf16(acc[8 * b + 2] + bf_lo(u.y), acc[8 * b + 3] + bf_hi(u.y)),
                      pack_bf16(acc[8 * b + 4] + bf_lo(u.z), acc[8 * b + 5] + bf_hi(u.z)),
                      pack_bf16(acc[8 * b + 6] + bf_lo(u.w), acc[8 * b + 7] + bf_hi(u.w)));
            }
            asm volatile("fence.proxy.async.shared::cta;" ::: "memory");
            __syncwarp();
            if (lane == 0) {
                tma_store2d(&P.om, ws + 3 * 8192 + (w & 3) * 2048, 64 * bj, bi * 128 + w * 16);
                asm volatile("cp.async.bulk.commit_group;" ::: "memory");
                asm volatile("cp.async.bulk.wait_group.read 0;" ::: "memory");
            }
        }
        PROF(11);
        if (tid == 0) g_epoch[blockIdx.x * 32] = epoch + 1;
    }
}

typedef CUresult (*EncodeFn)(CUtensorMap*, CUtensorMapDataType, cuuint32_t, void*, const cuuint64_t*, const cuuint64_t*,
                             const cuuint32_t*, const cuuint32_t*, CUtensorMapInterleave, CUtensorMapSwizzle,
                             CUtensorMapL2promotion, CUtensorMapFloatOOBfill);

void make2d(EncodeFn enc, CUtensorMap* tm, const void* ptr, int cols, int rows, int bc, int br, CUtensorMapSwizzle sw) {
    cuuint64_t gd[2] = {(cuuint64_t)cols, (cuuint64_t)rows};
    cuuint64_t gs[1] = {(cuuint64_t)cols * 2};
    cuuint32_t bd[2] = {(cuuint32_t)bc, (cuuint32_t)br};
    cuuint32_t es[2] = {1, 1};
    enc(tm, CU_TENSOR_MAP_DATA_TYPE_BFLOAT16, 2, const_cast<void*>(ptr), gd, gs, bd, es, CU_TENSOR_MAP_INTERLEAVE_NONE, sw,
        CU_TENSOR_MAP_L2_PROMOTION_L2_128B, CU_TENSOR_MAP_FLOAT_OOB_FILL_NONE);
}

}

extern "C" void kernel_launch(void* const* d_in, const int* in_sizes, int n_in, void* d_out, int out_size) {
    (void)in_sizes; (void)n_in; (void)out_size;
    static EncodeFn enc = nullptr;
    if (!enc) {
        void* fn = nullptr;
        cudaDriverEntryPointQueryResult qr;
        cudaGetDriverEntryPoint("cuTensorMapEncodeTiled", &fn, cudaEnableDefault, &qr);
        enc = (EncodeFn)fn;
        cudaFuncSetAttribute(fused_block_kernel, cudaFuncAttributeMaxDynamicSharedMemorySize, SMEM_BYTES);
    }
    Params P;
    make2d(enc, &P.xm, d_in[0], DM, 2048, 64, 128, CU_TENSOR_MAP_SWIZZLE_128B);
    make2d(enc, &P.qkv, d_in[1], 3 * DM, DM, 64, 128, CU_TENSOR_MAP_SWIZZLE_128B);
    make2d(enc, &P.wo, d_in[2], DM, DM, 64, 128, CU_TENSOR_MAP_SWIZZLE_128B);
    make2d(enc, &P.wg, d_in[4], FF, DM, 64, 64, CU_TENSOR_MAP_SWIZZLE_128B);
    make2d(enc, &P.wu, d_in[5], FF, DM, 64, 64, CU_TENSOR_MAP_SWIZZLE_128B);
    make2d(enc, &P.wg2, d_in[4], FF, DM, 32, 128, CU_TENSOR_MAP_SWIZZLE_64B);
    make2d(enc, &P.wu2, d_in[5], FF, DM, 32, 128, CU_TENSOR_MAP_SWIZZLE_64B);
    make2d(enc, &P.wd, d_in[6], DM, FF, 64, 64, CU_TENSOR_MAP_SWIZZLE_128B);
    make2d(enc, &P.wd2, d_in[6], DM, FF, 64, 32, CU_TENSOR_MAP_SWIZZLE_128B);
    make2d(enc, &P.om, d_out, DM, 2048, 64, 16, CU_TENSOR_MAP_SWIZZLE_128B);
    P.zero = 0;
    fused_block_kernel<<<NCTA, 384, SMEM_BYTES>>>(P);
}
```

```cpp
#include <cuda_runtime.h>
#include <cuda_bf16.h>
#include <cuda.h>
#include <stdint.h>

namespace {

constexpr int DM = 512, FF = 1792;
constexpr int NBLK = 16, NJ = 8, NCTA = NBLK * NJ;
constexpr int STAGE_BYTES = 16384;
constexpr int SM_K = 8 * STAGE_BYTES;
constexpr int KVH = 24576;
constexpr int SM_BAR = SM_K + 4 * KVH;
constexpr int SMEM_BYTES = SM_BAR + 768;

constexpr int B_FULL = 0, B_EMPTY = 64, B_X = 128, B_XCH = 192, B_K = 256, B_V = 288, B_XFREE = 320, B_DEAD = 328, B_PUB = 352,
              B_WG = 384, B_LVL = 640, B_XR = 672;
constexpr int SM_EPOCH = 664;
constexpr int W_INO = 0, W_O3 = 8, W_INH = 16, W_INA = 48, W_H2 = 104, W_HDEAD = 112;
#define UNLIKELY(x) __builtin_expect(!!(x), 0)
constexpr int LEAD = 1;
constexpr uint32_t SMD = 1024;

struct Params {
    CUtensorMap xm, qkv, wo, wg, wu, wg2, wu2, wd, wd2;
};

extern __shared__ __align__(1024) uint8_t smem_raw[];

struct Scratch {
    uint4 kv[NCTA * 2 * 4 * 8 * 32];
    uint4 o[NBLK * 8 * 32 * 32];
    uint4 h[NBLK * 8 * 32 * 32];
    uint4 stat[NBLK * 8 * 8 * 8];
};
struct Global {
    Scratch scr[2];
    uint4 hff[NCTA * 2 * 4 * 512];
    unsigned flagF[NCTA * 32];
    unsigned epoch[NCTA * 32];
};
__device__ __align__(1024) Global g_mem;

__device__ __forceinline__ uint32_t smem_u32(const void* p) { return (uint32_t)__cvta_generic_to_shared(p); }
__device__ __forceinline__ void mbar_init(uint32_t b, uint32_t c) {
    asm volatile("mbarrier.init.shared::cta.b64 [%0], %1;" ::"r"(b), "r"(c) : "memory");
}
__device__ __forceinline__ void mbar_expect(uint32_t b, uint32_t bytes) {
    asm volatile("mbarrier.arrive.expect_tx.shared::cta.b64 _, [%0], %1;" ::"r"(b), "r"(bytes) : "memory");
}
__device__ __forceinline__ void mbar_arrive(uint32_t b) {
    asm volatile("mbarrier.arrive.shared::cta.b64 _, [%0];" ::"r"(b) : "memory");
}
__device__ __forceinline__ void mbar_wait(uint32_t b, uint32_t ph) {
    asm volatile(
        "{\n.reg .pred p;\n.reg .u32 n;\n"
        "mov.u32 n, 0;\n"
        "LOOP:\n"
        "mbarrier.try_wait.parity.shared::cta.b64 p, [%0], %1;\n"
        "add.u32 n, n, 1;\n"
        "setp.lt.and.u32 p, n, 262144, !p;\n"
        "@p bra LOOP;\n}"
        ::"r"(b), "r"(ph) : "memory");
}
__device__ __forceinline__ bool mbar_test2(uint32_t b0, uint32_t b1) {
    uint32_t r;
    asm volatile(
        "{\n.reg .pred p, q;\n"
        "mbarrier.test_wait.parity.shared::cta.b64 p, [%1], 0;\n"
        "mbarrier.test_wait.parity.shared::cta.b64 q, [%2], 0;\n"
        "and.pred p, p, q;\n"
        "selp.u32 %0, 1, 0, p;\n}"
        : "=r"(r) : "r"(b0), "r"(b1) : "memory");
    return r != 0;
}
__device__ __forceinline__ unsigned ld_acquire(const unsigned* p) {
    unsigned v;
    asm volatile("ld.acquire.gpu.global.u32 %0, [%1];" : "=r"(v) : "l"(p) : "memory");
    return v;
}
__device__ __forceinline__ void flag_set(unsigned* p, unsigned v) {
    asm volatile("st.relaxed.gpu.global.u32 [%0], %1;" ::"l"(p), "r"(v) : "memory");
}
__device__ __forceinline__ uint4 ld_ll(const uint4* p) {
    uint4 v;
    asm volatile("{\n.reg .b128 t;\n.reg .b64 a, b;\nld.relaxed.gpu.global.b128 t, [%4];\nmov.b128 {a, b}, t;\n"
                 "mov.b64 {%0,%1}, a;\nmov.b64 {%2,%3}, b;\n}" : "=r"(v.x), "=r"(v.y), "=r"(v.z), "=r"(v.w) : "l"(p) : "memory");
    return v;
}
__device__ __forceinline__ uint32_t ld_ll1(const uint32_t* p) {
    uint32_t v;
    asm volatile("ld.relaxed.gpu.global.u32 %0, [%1];" : "=r"(v) : "l"(p) : "memory");
    return v;
}
__device__ __forceinline__ void ld_ll4(uint32_t (&r)[4], const uint4* p) {
    const uint4 v = ld_ll(p);
    r[0] = v.x; r[1] = v.y; r[2] = v.z; r[3] = v.w;
}
__device__ __forceinline__ void st_ll(uint4* p, uint32_t a, uint32_t b, uint32_t c, uint32_t d) {
    asm volatile("{\n.reg .b128 t;\n.reg .b64 a, b;\nmov.b64 a, {%1,%2};\nmov.b64 b, {%3,%4};\nmov.b128 t, {a, b};\n"
                 "st.relaxed.gpu.global.b128 [%0], t;\n}" ::"l"(p), "r"(a), "r"(b), "r"(c), "r"(d) : "memory");
}
constexpr int SPIN_LIMIT = 100000;
__device__ __forceinline__ uint32_t nz(uint32_t v) {
    uint32_t r;
    asm("max.u32 %0, %1, 1;" : "=r"(r) : "r"(v));
    return r;
}
__device__ __forceinline__ uint32_t umin4(uint32_t m, const uint4& r) { return min(m, r.w); }
__device__ __forceinline__ bool warp_bad(uint32_t m) { return __any_sync(0xffffffffu, m == 0); }
template <int T0> __device__ __forceinline__ bool bad8(const uint32_t (&a)[32][4]) {
    const uint32_t m = __vimin3_u32(__vimin3_u32(a[T0][3], a[T0 + 1][3], a[T0 + 2][3]), __vimin3_u32(a[T0 + 3][3], a[T0 + 4][3], a[T0 + 5][3]),
                                    min(a[T0 + 6][3], a[T0 + 7][3]));
    return warp_bad(m);
}
template <int T0>
__device__ __forceinline__ void validate8(uint32_t (&a)[32][4], const uint4* src) {
    if (UNLIKELY(bad8<T0>(a))) {
#pragma unroll 1
        for (int it = 0;; it++) {
#pragma unroll
            for (int k = 0; k < 8; k++) ld_ll4(a[T0 + k], src + k * 32);
            if (!bad8<T0>(a) || it >= SPIN_LIMIT) break;
        }
    }
}
__device__ __forceinline__ void cp_async16(uint32_t dst, const void* src) {
    asm volatile("cp.async.cg.shared.global [%0], [%1], 16;" ::"r"(dst), "l"(src) : "memory");
}
__device__ __forceinline__ void lds4(uint32_t (&r)[4], uint32_t addr) {
    asm volatile("ld.shared.v4.u32 {%0,%1,%2,%3}, [%4];" : "=r"(r[0]), "=r"(r[1]), "=r"(r[2]), "=r"(r[3]) : "r"(addr) : "memory");
}
__device__ __forceinline__ uint4 lds128(uint32_t addr);
template <int T0> __device__ __forceinline__ void lds8(uint32_t (&a)[32][4], uint32_t sa) {
#pragma unroll
    for (int k = 0; k < 8; k++) lds4(a[T0 + k], sa + k * 512);
}
template <int T0>
__device__ __forceinline__ void check8(uint32_t (&a)[32][4], uint32_t sa, const uint4* src) {
    if (UNLIKELY(bad8<T0>(a))) {
#pragma unroll 1
        for (int it = 0; it < SPIN_LIMIT; it++) {
#pragma unroll 1
            for (int k = 0; k < 8; k++) cp_async16(sa + k * 512, src + k * 32);
            asm volatile("cp.async.wait_all;" ::: "memory");
            uint32_t m = 0xffffffffu;
#pragma unroll 1
            for (int k = 0; k < 8; k++) m = umin4(m, lds128(sa + k * 512));
            if (!warp_bad(m)) break;
        }
        lds8<T0>(a, sa);
    }
}
__device__ __forceinline__ void ld_cg4(uint32_t (&r)[4], const uint4* p) {
    asm volatile("ld.global.cg.v4.u32 {%0,%1,%2,%3}, [%4];" : "=r"(r[0]), "=r"(r[1]), "=r"(r[2]), "=r"(r[3]) : "l"(p) : "memory");
}
__device__ __forceinline__ void stg128(uint4* p, uint32_t a, uint32_t b, uint32_t c, uint32_t d) {
    asm volatile("st.global.v4.u32 [%0], {%1,%2,%3,%4};" ::"l"(p), "r"(a), "r"(b), "r"(c), "r"(d) : "memory");
}
__device__ __forceinline__ uint32_t mapa(uint32_t addr, uint32_t rank) {
    uint32_t r;
    asm("mapa.shared::cluster.u32 %0, %1, %2;" : "=r"(r) : "r"(addr), "r"(rank));
    return r;
}
__device__ __forceinline__ void st_async4(uint32_t addr, uint32_t bar, uint32_t a, uint32_t b, uint32_t c, uint32_t d) {
    asm volatile("st.async.shared::cluster.mbarrier::complete_tx::bytes.v4.b32 [%0], {%2,%3,%4,%5}, [%1];"
                 ::"r"(addr), "r"(bar), "r"(a), "r"(b), "r"(c), "r"(d) : "memory");
}
__device__ __forceinline__ void stsm4(uint32_t addr, uint32_t a, uint32_t b, uint32_t c, uint32_t d) {
    asm volatile("stmatrix.sync.aligned.m8n8.x4.shared.b16 [%0], {%1,%2,%3,%4};" ::"r"(addr), "r"(a), "r"(b), "r"(c), "r"(d) : "memory");
}
__device__ __forceinline__ void mbar_wait_cluster(uint32_t b, uint32_t ph) {
    asm volatile(
        "{\n.reg .pred p;\n.reg .u32 n;\n"
        "mov.u32 n, 0;\n"
        "LOOP:\n"
        "mbarrier.try_wait.parity.acquire.cluster.shared::cta.b64 p, [%0], %1;\n"
        "add.u32 n, n, 1;\n"
        "setp.lt.and.u32 p, n, 262144, !p;\n"
        "@p bra LOOP;\n}"
        ::"r"(b), "r"(ph) : "memory");
}
__device__ __forceinline__ uint32_t tie(uint32_t x, uint32_t dep, uint32_t zero) {
    uint32_t r;
    asm("lop3.b32 %0, %1, %2, %3, 0xF8;" : "=r"(r) : "r"(x), "r"(dep), "r"(zero));
    return r;
}
__device__ __forceinline__ void ldsm4(uint32_t (&r)[4], uint32_t addr) {
    asm volatile("ldmatrix.sync.aligned.m8n8.x4.shared.b16 {%0,%1,%2,%3}, [%4];"
                 : "=r"(r[0]), "=r"(r[1]), "=r"(r[2]), "=r"(r[3]) : "r"(addr) : "memory");
}
__device__ __forceinline__ void sts128(uint32_t addr, uint32_t a, uint32_t b, uint32_t c, uint32_t d) {
    asm volatile("st.shared.v4.u32 [%0], {%1,%2,%3,%4};" ::"r"(addr), "r"(a), "r"(b), "r"(c), "r"(d) : "memory");
}
__device__ __forceinline__ uint4 lds128(uint32_t addr) {
    uint4 v;
    asm volatile("ld.shared.v4.u32 {%0,%1,%2,%3}, [%4];" : "=r"(v.x), "=r"(v.y), "=r"(v.z), "=r"(v.w) : "r"(addr) : "memory");
    return v;
}
#define ELECTED "{\n.reg .pred e;\nelect.sync _|e, 0xffffffff;\n@e "
__device__ __forceinline__ void mbar_expect_w(uint32_t b, uint32_t bytes) {
    asm volatile(ELECTED "mbarrier.arrive.expect_tx.shared::cta.b64 _, [%0], %1;\n}" ::"r"(b), "r"(bytes) : "memory");
}
__device__ __forceinline__ void tma2d(uint32_t dst, const CUtensorMap* tm, uint32_t bar, int c0, int c1) {
    asm volatile(ELECTED "cp.async.bulk.tensor.2d.shared::cluster.global.mbarrier::complete_tx::bytes [%0], [%1, {%3,%4}], [%2];\n}"
                 ::"r"(dst), "l"(tm), "r"(bar), "r"(c0), "r"(c1) : "memory");
}
__device__ __forceinline__ void mbar_arrive_remote(uint32_t b) {
    asm volatile("mbarrier.arrive.shared::cluster.b64 _, [%0];" ::"r"(b) : "memory");
}
__device__ __forceinline__ void tma4d(uint32_t dst, const CUtensorMap* tm, uint32_t bar, int c0, int c2) {
    asm volatile(ELECTED "cp.async.bulk.tensor.4d.shared::cluster.global.mbarrier::complete_tx::bytes [%0], [%1, {%3,%5,%4,%5}], [%2];\n}"
                 ::"r"(dst), "l"(tm), "r"(bar), "r"(c0), "r"(c2), "r"(0) : "memory");
}
__device__ __forceinline__ void bulk_g2s(uint32_t dst, const void* src, uint32_t bytes, uint32_t bar) {
    asm volatile(ELECTED "cp.async.bulk.shared::cluster.global.mbarrier::complete_tx::bytes [%0], [%1], %2, [%3];\n}"
                 ::"r"(dst), "l"(src), "r"(bytes), "r"(bar) : "memory");
}
__device__ __forceinline__ void bulk_g2s_pair(uint32_t dst, const void* src, uint32_t bytes, uint32_t bar) {
    asm volatile(ELECTED "cp.async.bulk.shared::cluster.global.mbarrier::complete_tx::bytes.multicast::cluster [%0], [%1], %2, [%3], %4;\n}"
                 ::"r"(dst), "l"(src), "r"(bytes), "r"(bar), "h"((uint16_t)3) : "memory");
}
__device__ __forceinline__ void bulk_s2g(void* dst, uint32_t src, uint32_t bytes) {
    asm volatile(ELECTED "cp.async.bulk.global.shared::cta.bulk_group [%0], [%1], %2;\n}" ::"l"(dst), "r"(src), "r"(bytes) : "memory");
}
__device__ __forceinline__ void prefetch_tmap(const CUtensorMap* tm) {
    asm volatile("prefetch.tensormap [%0];" ::"l"(tm) : "memory");
}
__device__ __forceinline__ uint32_t pack_bf16(float lo, float hi) {
    uint32_t r;
    asm("cvt.rn.bf16x2.f32 %0, %1, %2;" : "=r"(r) : "f"(hi), "f"(lo));
    return r;
}
__device__ __forceinline__ float bf_lo(uint32_t v) { return __uint_as_float(v << 16); }
__device__ __forceinline__ float bf_hi(uint32_t v) { return __uint_as_float(v & 0xffff0000u); }
__device__ __forceinline__ uint32_t badd2(uint32_t a, uint32_t b) {
    uint32_t r;
    asm("add.rn.bf16x2 %0, %1, %2;" : "=r"(r) : "r"(a), "r"(b));
    return r;
}
__device__ __forceinline__ float ex2(float x) {
    float r;
    asm("ex2.approx.ftz.f32 %0, %1;" : "=f"(r) : "f"(x));
    return r;
}
__device__ __forceinline__ float relu2(float x) { return x + fabsf(x); }
__device__ __forceinline__ float rcp(float x) {
    float r;
    asm("rcp.approx.ftz.f32 %0, %1;" : "=f"(r) : "f"(x));
    return r;
}
__device__ __forceinline__ uint4 ldsm4n(uint32_t addr) {
    uint4 v;
    asm volatile("ldmatrix.sync.aligned.m8n8.x4.shared.b16 {%0,%1,%2,%3}, [%4];"
                 : "=r"(v.x), "=r"(v.y), "=r"(v.z), "=r"(v.w) : "r"(addr) : "memory");
    return v;
}
__device__ __forceinline__ uint4 ldsm4t(uint32_t addr) {
    uint4 v;
    asm volatile("ldmatrix.sync.aligned.m8n8.x4.trans.shared.b16 {%0,%1,%2,%3}, [%4];"
                 : "=r"(v.x), "=r"(v.y), "=r"(v.z), "=r"(v.w) : "r"(addr) : "memory");
    return v;
}
__device__ __forceinline__ void mma16816(float& d0, float& d1, float& d2, float& d3, uint32_t a0, uint32_t a1, uint32_t a2,
                                         uint32_t a3, uint32_t b0, uint32_t b1) {
    asm("mma.sync.aligned.m16n8k16.row.col.f32.bf16.bf16.f32 {%0,%1,%2,%3},{%4,%5,%6,%7},{%8,%9},{%0,%1,%2,%3};"
        : "+f"(d0), "+f"(d1), "+f"(d2), "+f"(d3) : "r"(a0), "r"(a1), "r"(a2), "r"(a3), "r"(b0), "r"(b1));
}
__device__ __forceinline__ void mma16816_z(float& d0, float& d1, float& d2, float& d3, uint32_t a0, uint32_t a1, uint32_t a2,
                                           uint32_t a3, uint32_t b0, uint32_t b1) {
    asm("mma.sync.aligned.m16n8k16.row.col.f32.bf16.bf16.f32 {%0,%1,%2,%3},{%4,%5,%6,%7},{%8,%9},{%10,%10,%10,%10};"
        : "=f"(d0), "=f"(d1), "=f"(d2), "=f"(d3) : "r"(a0), "r"(a1), "r"(a2), "r"(a3), "r"(b0), "r"(b1), "f"(0.f));
}
__device__ __forceinline__ void vmma(float* d, const uint32_t (&a)[4], uint32_t b0, uint32_t b1) {
    asm volatile("mma.sync.aligned.m16n8k16.row.col.f32.bf16.bf16.f32 {%0,%1,%2,%3},{%4,%5,%6,%7},{%8,%9},{%0,%1,%2,%3};"
                 : "+f"(d[0]), "+f"(d[1]), "+f"(d[2]), "+f"(d[3]) : "r"(a[0]), "r"(a[1]), "r"(a[2]), "r"(a[3]), "r"(b0), "r"(b1));
}
__device__ __forceinline__ void vmma_c(float* d, const uint32_t (&a)[4], uint32_t b0, uint32_t b1, float c) {
    asm volatile("mma.sync.aligned.m16n8k16.row.col.f32.bf16.bf16.f32 {%0,%1,%2,%3},{%4,%5,%6,%7},{%8,%9},{%10,%10,%10,%10};"
                 : "=f"(d[0]), "=f"(d[1]), "=f"(d[2]), "=f"(d[3]) : "r"(a[0]), "r"(a[1]), "r"(a[2]), "r"(a[3]), "r"(b0), "r"(b1), "f"(c));
}
__device__ __forceinline__ void vex2(float& x) { asm volatile("ex2.approx.ftz.f32 %0, %0;" : "+f"(x)); }
__device__ __forceinline__ uint32_t vpack(float lo, float hi) {
    uint32_t r;
    asm volatile("cvt.rn.bf16x2.f32 %0, %1, %2;" : "=r"(r) : "f"(hi), "f"(lo));
    return r;
}
__device__ __forceinline__ void wg_fence() { asm volatile("wgmma.fence.sync.aligned;" ::: "memory"); }
__device__ __forceinline__ void wg_commit() { asm volatile("wgmma.commit_group.sync.aligned;" ::: "memory"); }
template <int N> __device__ __forceinline__ void wg_wait() { asm volatile("wgmma.wait_group.sync.aligned %0;" ::"n"(N) : "memory"); }
__device__ __forceinline__ void bar_sync(int id, int n) { asm volatile("bar.sync %0, %1;" ::"r"(id), "r"(n) : "memory"); }
__device__ __forceinline__ void bar_arrive(int id, int n) { asm volatile("bar.arrive %0, %1;" ::"r"(id), "r"(n) : "memory"); }

constexpr uint32_t DESC_HI_128 = (1024 >> 4) | (1u << 30);
constexpr uint32_t DESC_HI_64 = (512 >> 4) | (2u << 30);
constexpr uint32_t DESC_LBO = (8192 >> 4) << 16;
__device__ __forceinline__ uint64_t make_desc(uint32_t lo, uint32_t hi) { return ((uint64_t)hi << 32) | lo; }

#define R8(a, o) "+f"(a[o]), "+f"(a[o + 1]), "+f"(a[o + 2]), "+f"(a[o + 3]), "+f"(a[o + 4]), "+f"(a[o + 5]), "+f"(a[o + 6]), "+f"(a[o + 7])

template <int ND>
__device__ __forceinline__ void wgmma_n64(float (&d)[ND], const uint32_t (&a)[4], uint64_t desc, int acc) {
    asm volatile(
        "{\n.reg .pred p;\nsetp.ne.b32 p, %37, 0;\n"
        "wgmma.mma_async.sync.aligned.m64n64k16.f32.bf16.bf16 "
        "{%0,%1,%2,%3,%4,%5,%6,%7,%8,%9,%10,%11,%12,%13,%14,%15,%16,%17,%18,%19,%20,%21,%22,%23,%24,%25,%26,%27,%28,%29,%30,%31},"
        "{%32,%33,%34,%35}, %36, p, 1, 1, 1;\n}"
        : R8(d, 0), R8(d, 8), R8(d, 16), R8(d, 24)
        : "r"(a[0]), "r"(a[1]), "r"(a[2]), "r"(a[3]), "l"(desc), "r"(acc));
}
__device__ __forceinline__ void wgmma_n128(float (&d)[64], const uint32_t (&a)[4], uint64_t desc, int acc) {
    asm volatile(
        "{\n.reg .pred p;\nsetp.ne.b32 p, %69, 0;\n"
        "wgmma.mma_async.sync.aligned.m64n128k16.f32.bf16.bf16 "
        "{%0,%1,%2,%3,%4,%5,%6,%7,%8,%9,%10,%11,%12,%13,%14,%15,%16,%17,%18,%19,%20,%21,%22,%23,%24,%25,%26,%27,%28,%29,%30,%31,"
        "%32,%33,%34,%35,%36,%37,%38,%39,%40,%41,%42,%43,%44,%45,%46,%47,%48,%49,%50,%51,%52,%53,%54,%55,%56,%57,%58,%59,%60,%61,%62,%63},"
        "{%64,%65,%66,%67}, %68, p, 1, 1, 1;\n}"
        : R8(d, 0), R8(d, 8), R8(d, 16), R8(d, 24), R8(d, 32), R8(d, 40), R8(d, 48), R8(d, 56)
        : "r"(a[0]), "r"(a[1]), "r"(a[2]), "r"(a[3]), "l"(desc), "r"(acc));
}
__device__ __forceinline__ void wgmma_n128_ss(float (&d)[64], uint64_t da, uint64_t db, int acc) {
    asm volatile(
        "{\n.reg .pred p;\nsetp.ne.b32 p, %66, 0;\n"
        "wgmma.mma_async.sync.aligned.m64n128k16.f32.bf16.bf16 "
        "{%0,%1,%2,%3,%4,%5,%6,%7,%8,%9,%10,%11,%12,%13,%14,%15,%16,%17,%18,%19,%20,%21,%22,%23,%24,%25,%26,%27,%28,%29,%30,%31,"
        "%32,%33,%34,%35,%36,%37,%38,%39,%40,%41,%42,%43,%44,%45,%46,%47,%48,%49,%50,%51,%52,%53,%54,%55,%56,%57,%58,%59,%60,%61,%62,%63},"
        "%64, %65, p, 1, 1, 0, 1;\n}"
        : R8(d, 0), R8(d, 8), R8(d, 16), R8(d, 24), R8(d, 32), R8(d, 40), R8(d, 48), R8(d, 56)
        : "l"(da), "l"(db), "r"(acc));
}
template <int N> __device__ __forceinline__ void fence_regs(float (&d)[N]) {
#pragma unroll
    for (int k = 0; k < N; k++) asm volatile("" : "+f"(d[k])::"memory");
}

struct Ctx {
    uint32_t sm;
    uint32_t bars;
    int lane;
    uint32_t zero;
};

template <int S, int T0, int KSTEP, uint32_t HI, int KEEP = 0, int ND>
__device__ __forceinline__ void stage_n64(const Ctx& c, float (&acc)[ND], const uint32_t (&a)[32][4]) {
    if (KEEP != 2) mbar_wait(c.bars + B_FULL + (S & 7) * 8, (S >> 3) & 1);
    wg_fence();
    constexpr uint32_t lo = ((SMD + (S & 7) * STAGE_BYTES) >> 4) | DESC_LBO;
#pragma unroll
    for (int k = 0; k < 8; k++) wgmma_n64(acc, a[T0 + k], make_desc(lo + k * (KSTEP >> 4), HI), (KEEP | T0 | k) != 0);
    wg_commit();
}
template <int S> __device__ __forceinline__ void release(const Ctx& c) {
    if (c.lane == 0) mbar_arrive(c.bars + B_EMPTY + (S & 7) * 8);
}
__device__ __forceinline__ void centre(uint32_t (&f)[4], uint32_t nm0, uint32_t nm1) {
    f[0] = badd2(f[0], nm0); f[2] = badd2(f[2], nm0);
    f[1] = badd2(f[1], nm1); f[3] = badd2(f[3], nm1);
}

__device__ __forceinline__ void qk_block(float (&s)[8], const uint32_t (&q)[4], uint32_t ka) {
    const uint4 kf = ldsm4n(ka);
    mma16816_z(s[0], s[1], s[2], s[3], q[0], q[1], q[2], q[3], kf.x, kf.y);
    mma16816_z(s[4], s[5], s[6], s[7], q[0], q[1], q[2], q[3], kf.z, kf.w);
}
__device__ __forceinline__ void pv_block(float (&o)[8], const uint32_t (&p)[4], uint32_t va) {
    const uint4 vf = ldsm4t(va);
    mma16816(o[0], o[1], o[2], o[3], p[0], p[1], p[2], p[3], vf.x, vf.y);
    mma16816(o[4], o[5], o[6], o[7], p[0], p[1], p[2], p[3], vf.z, vf.w);
}

__device__ __forceinline__ void attention(const Ctx& c, uint32_t (&q)[4][4], int bi, int w, uint4* go, uint32_t (&a)[32][4],
                                          const uint4* osrc) {
    const int lane = c.lane, g = lane >> 2, cq = lane & 3;
    const bool p0 = 2 * cq > g, p1 = 2 * cq + 1 > g;
    const uint32_t dmask = (p0 ? 0u : 0xffffu) | (p1 ? 0u : 0xffff0000u);
    const int tmin = 16 - 8 * bi - w;
    const uint32_t omask = tmin > 0 ? 0u : 0xffffffffu;
    const float lstart = -16.f * (float)max(tmin - 1, 0);
    constexpr uint32_t ONES = 0x3f803f80u;
    const uint32_t kv0 = c.sm + SM_K + w * 512 + lane * 16;
    float sa[8] = {}, sb[8], o[8], l[4], lm[4] = {};
    uint4 kf = {}, vf = {};
    auto step = [&](float (&x)[8], float (&z)[8], bool qk, bool ldk, uint32_t kn, bool ldv, uint32_t vn) {
        uint32_t p[4];
        vex2(x[0]);
        p[0] = vpack(z[0], z[1]);
        p[1] = vpack(z[2], z[3]);
        vex2(x[1]);
        if (qk) vmma_c(z, q[0], kf.x, kf.y, 0.f);
        vex2(x[2]);
        p[2] = vpack(z[4], z[5]);
        p[3] = vpack(z[6], z[7]);
        vex2(x[3]);
        if (qk) vmma_c(z + 4, q[0], kf.z, kf.w, 0.f);
        if (ldk) kf = ldsm4n(kn);
        vex2(x[4]);
        vmma(l, p, ONES, ONES);
        vex2(x[5]);
        vmma(o, p, vf.x, vf.y);
        vex2(x[6]);
        vmma(o + 4, p, vf.z, vf.w);
        if (ldv) vf = ldsm4t(vn);
        vex2(x[7]);
    };
    auto step1 = [&](uint32_t ks, float (&on)[8], float (&ln)[4]) {
        const uint32_t vs = ks + KVH / 2;
        const uint4 v0 = ldsm4t(vs), vd = ldsm4t(vs + 16 * 512);
        vex2(sb[0]);
        const uint32_t m0 = vpack(sa[0], sa[1]), m1 = vpack(sa[2], sa[3]);
        vex2(sb[1]);
        vmma_c(sa, q[0], kf.x, kf.y, 0.f);
        vex2(sb[2]);
        const uint32_t m2 = vpack(sa[4], sa[5]), m3 = vpack(sa[6], sa[7]);
        vmma_c(sa + 4, q[0], kf.z, kf.w, 0.f);
        kf = ldsm4n(ks + 3 * 512);
        vf = ldsm4t(vs + 512);
        const uint32_t po[4] = {m0 & ~dmask, 0u, m2, m3 & ~dmask}, pd[4] = {m0 & dmask, m1, 0u, m3 & dmask};
        const uint32_t pm[4] = {m0 & (dmask | omask), m1, m2 & omask, m3 & (dmask | omask)};
        vex2(sb[3]);
        vmma_c(on, po, v0.x, v0.y, 0.f);
        vex2(sb[4]);
        vmma_c(on + 4, po, v0.z, v0.w, 0.f);
        vex2(sb[5]);
        vmma_c(ln, pm, ONES, ONES, 0.f);
        vex2(sb[6]);
        vmma(on, pd, vd.x, vd.y);
        vmma(on + 4, pd, vd.z, vd.w);
        vex2(sb[7]);
    };
    auto merge = [&](const float (&d)[8]) {
        sa[0] = p0 ? sa[0] : d[0]; sa[1] = p1 ? sa[1] : d[1]; sa[2] = d[2]; sa[3] = d[3];
        sa[6] = p0 ? sa[6] : d[6]; sa[7] = p1 ? sa[7] : d[7];
    };
    auto finish = [&](int hp, const uint32_t (&qp)[4]) {
        float l0 = l[0] + lm[0], l1 = l[2] + lm[2];
        float i0 = rcp(l0), i1 = rcp(l1);
        uint32_t r[4];
#pragma unroll
        for (int e = 0; e < 4; e++) r[e] = pack_bf16(o[2 * e] * ((e & 1) ? i1 : i0), o[2 * e + 1] * ((e & 1) ? i1 : i0));
#pragma unroll
        for (int e = 0; e < 4; e++) { l0 = fmaf(o[2 * e], 0.f, l0); l1 = fmaf(o[2 * e + 1], 0.f, l1); }
        if (UNLIKELY(__any_sync(0xffffffffu, max(__float_as_uint(l0) - 0x2b800000u, __float_as_uint(l1) - 0x2b800000u) > 0x28000000u))) {
            const uint32_t kp = kv0 + hp * KVH;
            float m0 = -INFINITY, m1 = -INFINITY;
#pragma unroll 1
            for (int pass = 0; pass < 2; pass++) {
#pragma unroll
                for (int e = 0; e < 8; e++) o[e] = 0.f;
                l[0] = l[1] = l[2] = l[3] = 0.f;
#pragma unroll 1
                for (int t = max(tmin, 0); t < 17; t++) {
                    float s[8];
                    qk_block(s, qp, kp + t * 512);
                    const bool lo = t > 0, hi = t < 16;
                    s[0] = (p0 ? hi : lo) ? s[0] : -INFINITY; s[6] = (p0 ? hi : lo) ? s[6] : -INFINITY;
                    s[1] = (p1 ? hi : lo) ? s[1] : -INFINITY; s[7] = (p1 ? hi : lo) ? s[7] : -INFINITY;
                    s[2] = lo ? s[2] : -INFINITY; s[3] = lo ? s[3] : -INFINITY;
                    s[4] = hi ? s[4] : -INFINITY; s[5] = hi ? s[5] : -INFINITY;
                    if (pass == 0) {
                        m0 = fmaxf(m0, fmaxf(fmaxf(s[0], s[1]), fmaxf(s[4], s[5])));
                        m1 = fmaxf(m1, fmaxf(fmaxf(s[2], s[3]), fmaxf(s[6], s[7])));
                    } else {
                        const uint32_t p[4] = {pack_bf16(ex2(s[0] - m0), ex2(s[1] - m0)), pack_bf16(ex2(s[2] - m1), ex2(s[3] - m1)),
                                               pack_bf16(ex2(s[4] - m0), ex2(s[5] - m0)), pack_bf16(ex2(s[6] - m1), ex2(s[7] - m1))};
                        pv_block(o, p, kp + KVH / 2 + t * 512);
                        mma16816(l[0], l[1], l[2], l[3], p[0], p[1], p[2], p[3], ONES, ONES);
                    }
                }
                m0 = fmaxf(m0, __shfl_xor_sync(0xffffffffu, m0, 1));
                m1 = fmaxf(m1, __shfl_xor_sync(0xffffffffu, m1, 1));
                m0 = fmaxf(m0, __shfl_xor_sync(0xffffffffu, m0, 2));
                m1 = fmaxf(m1, __shfl_xor_sync(0xffffffffu, m1, 2));
            }
            i0 = rcp(l[0]); i1 = rcp(l[2]);
#pragma unroll
            for (int e = 0; e < 4; e++) r[e] = pack_bf16(o[2 * e] * ((e & 1) ? i1 : i0), o[2 * e + 1] * ((e & 1) ? i1 : i0));
        }
        st_ll(go + hp * 1024, r[0], r[1], r[2], nz(r[3]));
    };
    mbar_wait(c.bars + B_K, 0);
    {
        float d[8];
        qk_block(sa, q[0], kv0);
        qk_block(d, q[0], kv0 + 16 * 512);
        qk_block(sb, q[0], kv0 + 512);
        kf = ldsm4n(kv0 + 2 * 512);
        merge(d);
#pragma unroll
        for (int e = 0; e < 8; e++) vex2(sa[e]);
    }
    l[0] = l[1] = l[2] = l[3] = lstart;
    {
        constexpr int D = 6;
        uint32_t pk[D][4];
        auto step_nov = [&](float (&x)[8], float (&z)[8], uint32_t (&p)[4], uint32_t kn, bool sum) {
            vex2(x[0]);
            p[0] = vpack(z[0], z[1]);
            p[1] = vpack(z[2], z[3]);
            vex2(x[1]);
            vmma_c(z, q[0], kf.x, kf.y, 0.f);
            vex2(x[2]);
            p[2] = vpack(z[4], z[5]);
            p[3] = vpack(z[6], z[7]);
            vex2(x[3]);
            vmma_c(z + 4, q[0], kf.z, kf.w, 0.f);
            kf = ldsm4n(kn);
            vex2(x[4]);
            vex2(x[5]);
            if (sum) vmma(l, p, ONES, ONES);
            vex2(x[6]);
            vex2(x[7]);
        };
#pragma unroll
        for (int t = 1; t <= D; t++) {
            if (t & 1) step_nov(sb, sa, pk[t - 1], kv0 + (t + 2) * 512, t > 1);
            else step_nov(sa, sb, pk[t - 1], kv0 + (t + 2) * 512, true);
        }
        mbar_wait(c.bars + B_V, 0);
        const uint32_t vs = kv0 + KVH / 2;
        {
            const uint4 v0 = ldsm4t(vs), vd = ldsm4t(vs + 16 * 512);
            vf = ldsm4t(vs + D * 512);
            const uint32_t* m = pk[0];
            const uint32_t po[4] = {m[0] & ~dmask, 0u, m[2], m[3] & ~dmask}, pd[4] = {m[0] & dmask, m[1], 0u, m[3] & dmask};
            const uint32_t pm[4] = {m[0] & (dmask | omask), m[1], m[2] & omask, m[3] & (dmask | omask)};
            vmma_c(lm, pm, ONES, ONES, 0.f);
            vmma_c(o, po, v0.x, v0.y, 0.f);
            vmma_c(o + 4, po, v0.z, v0.w, 0.f);
            vmma(o, pd, vd.x, vd.y);
            vmma(o + 4, pd, vd.z, vd.w);
        }
#pragma unroll
        for (int t = D + 1; t < 14; t++) {
            if (t & 1) step(sb, sa, true, true, kv0 + (t + 2) * 512, true, vs + t * 512);
            else step(sa, sb, true, true, kv0 + (t + 2) * 512, true, vs + t * 512);
#pragma unroll
            for (int k = 1 + (t - D - 1) * (D - 1) / (13 - D); k < 1 + (t - D) * (D - 1) / (13 - D); k++) {
                const uint4 vk = ldsm4t(vs + k * 512);
                vmma(o, pk[k], vk.x, vk.y);
                vmma(o + 4, pk[k], vk.z, vk.w);
            }
        }
    }
    bool ready = false;
#pragma unroll 1
    for (int h = 0; h < 3; h++) {
        const uint32_t ks = kv0 + h * KVH, vs = ks + KVH / 2;
        if (!ready) { mbar_wait(c.bars + B_K + (h + 1) * 8, 0); mbar_wait(c.bars + B_V + (h + 1) * 8, 0); }
        ready = mbar_test2(c.bars + B_K + min(h + 2, 3) * 8, c.bars + B_V + min(h + 2, 3) * 8);
        const uint32_t kn = ks + KVH;
        const uint4 kd = ldsm4n(kn + 16 * 512);
        step(sa, sb, true, true, kn, true, vs + 14 * 512);
        uint32_t qp[4];
#pragma unroll
        for (int e = 0; e < 4; e++) { qp[e] = q[0][e]; q[0][e] = q[1][e]; q[1][e] = q[2][e]; q[2][e] = q[3][e]; }
        {
            float d[8];
            vmma_c(d, q[0], kd.x, kd.y, 0.f);
            vmma_c(d + 4, q[0], kd.z, kd.w, 0.f);
            step(sb, sa, true, true, kn + 512, true, vs + 15 * 512);
            merge(d);
        }
        step(sa, sb, true, true, kn + 2 * 512, false, 0);
        float on[8], ln[4];
        step1(kn, on, ln);
        finish(h, qp);
#pragma unroll
        for (int e = 0; e < 8; e++) o[e] = on[e];
        lm[0] = ln[0]; lm[2] = ln[2];
        if (h >= 1 && lane == 0) mbar_arrive(c.bars + B_DEAD + (h - 1) * 8);
        if (h == 2 && lane == 0) mbar_arrive(c.bars + B_WG + (w >> 2) * 128 + W_H2);
        l[0] = l[1] = l[2] = l[3] = lstart;
#pragma unroll
        for (int t = 2; t < 14; t += 2) {
            step(sa, sb, true, true, kn + (t + 2) * 512, true, kn + KVH / 2 + t * 512);
            step(sb, sa, true, true, kn + (t + 3) * 512, true, kn + KVH / 2 + (t + 1) * 512);
        }
    }
    {
#pragma unroll
        for (int k = 0; k < 8; k++) ld_ll4(a[16 + k], osrc + 2048 + k * 32);
        const uint32_t vs = kv0 + 3 * KVH + KVH / 2;
        step(sa, sb, true, false, 0, true, vs + 14 * 512);
        step(sb, sa, false, false, 0, true, vs + 15 * 512);
        const uint32_t p[4] = {pack_bf16(sb[0], sb[1]), pack_bf16(sb[2], sb[3]), pack_bf16(sb[4], sb[5]), pack_bf16(sb[6], sb[7])};
        vmma(l, p, ONES, ONES);
        vmma(o, p, vf.x, vf.y);
        vmma(o + 4, p, vf.z, vf.w);
        finish(3, q[0]);
        mbar_wait(c.bars + B_WG + (w >> 2) * 128 + W_INO, 0);
        const uint32_t os = c.sm + SM_K + ((w >> 2) == LEAD ? 0 : 32768) + (w & 3) * 4096 + lane * 16;
        lds8<0>(a, os);
        lds8<8>(a, os + 16384);
    }
}

__device__ __forceinline__ void fill_a(const Global* G, uint32_t sm, uint32_t bars, int bi, int bj, int q, int wg) {
    const int sl = q < 6 ? q : q < 12 ? q - 6 : q - 12;
    const uint32_t bar = bars + B_WG + wg * 128 + W_INA + sl * 8, dst = sm + SM_K + wg * 49152 + sl * 8192;
    mbar_expect_w(bar, 8192);
    if (q < 12) {
        const int ck = q / 3 - 1, r = q - 3 * ck - 2;
        bulk_g2s(dst, G->hff + ((bi * 8 + ((bj + 2 * r) & 7)) * 8 + wg * 4 + ck) * 512, 8192, bar);
    } else {
        bulk_g2s(dst, G->hff + ((bi * 8 + ((bj + 4 * sl) & 7)) * 8 + wg * 4 + 3) * 512, 4096, bar);
        bulk_g2s(dst + 4096, G->hff + ((bi * 8 + ((bj + 4 * sl + 2) & 7)) * 8 + wg * 4 + 3) * 512, 4096, bar);
    }
}

__global__ void __cluster_dims__(2, 1, 1) __launch_bounds__(384, 1)
fused_block_kernel(Global* const G, const uint32_t zero, uint4* const outp, const __grid_constant__ Params P) {
    const uint32_t sm = smem_u32(smem_raw);
    const uint32_t bars = sm + SM_BAR;
    const int tid = threadIdx.x, lane = tid & 31;
    const int warp = __shfl_sync(0xffffffffu, tid >> 5, 0);
    int cta;
    {
        const int cl = blockIdx.x >> 1;
        const int t = cl - 36, r7 = (t * 37) >> 8, k7 = t - 7 * r7;
        const int k = cl < 4 ? 3 : cl < 36 ? (cl + 4) & 7 : k7 + (k7 >= 3);
        const int ord = cl < 4 ? cl + 4 : cl < 36 ? (cl - 4) >> 3 : r7 + 4;
        cta = ((k & 1) * 8 + ord) * 8 + (k >> 1) * 2 + (blockIdx.x & 1);
    }
    const int bi = cta >> 3, bj = cta & 7;
    if ((sm & 0x3ffffu) != SMD) return;

    if (warp == 8) {
        if (lane == 0) {
#pragma unroll
            for (int k = 0; k < 8; k++) mbar_init(bars + B_X + k * 8, 1);
            asm volatile("fence.mbarrier_init.release.cluster;" ::: "memory");
        }
        __syncwarp();
        bar_arrive(0, 384);
        {
#pragma unroll
            for (int kb = 0; kb < 8; kb++) {
                mbar_expect_w(bars + B_X + kb * 8, 16384);
                tma2d(sm + (kb < 6 ? SM_K + kb * 16384 : kb * STAGE_BYTES), &P.xm, bars + B_X + kb * 8, kb * 64, bi * 128);
            }
        }
        __syncwarp();
        asm volatile("barrier.cluster.arrive.relaxed.aligned;" ::: "memory");
        asm volatile("barrier.cluster.wait.aligned;" ::: "memory");
        bar_sync(1, 384);
    } else {
        if (lane == 0) {
            if (warp < 8) {
                mbar_init(bars + B_FULL + warp * 8, 1);
                mbar_init(bars + B_EMPTY + warp * 8, 8);
                mbar_init(bars + B_K + warp * 8, 10);
                mbar_init(bars + B_XCH + warp * 8, 1);
                mbar_expect(bars + B_XCH + warp * 8, 2048);
            } else if (warp == 9) {
                mbar_init(bars + B_XFREE, 9);
#pragma unroll
                for (int k = 0; k < 7; k++) mbar_init(bars + B_DEAD + k * 8, k == 2 ? 16 : 8);
#pragma unroll
                for (int k = 0; k < 3; k++) mbar_init(bars + B_LVL + k * 8, 1);
                mbar_init(bars + B_XR, 16);
            } else {
#pragma unroll
                for (int k = 0; k < 15; k++) mbar_init(bars + B_WG + (warp - 10) * 128 + k * 8, k < 13 ? 1 : 4);
#pragma unroll
                for (int k = 0; k < 4; k++) mbar_expect(bars + B_WG + (warp - 10) * 128 + W_INH + k * 8, 16384);
            }
            asm volatile("fence.mbarrier_init.release.cluster;" ::: "memory");
        }
        __syncwarp();
        bar_arrive(1, 384);
        asm volatile("barrier.cluster.arrive.relaxed.aligned;" ::: "memory");
        bar_sync(0, 384);
        asm volatile("barrier.cluster.wait.aligned;" ::: "memory");
    }

    if (warp >= 8) {
        asm volatile("setmaxnreg.dec.sync.aligned.u32 56;");
        if (warp == 8) {
            {
                int s = 0;
                auto acquire = [&]() -> uint32_t {
                    const int slot = s & 7;
                    mbar_wait(bars + B_EMPTY + slot * 8, ((s >> 3) - 1) & 1);
                    mbar_expect_w(bars + B_FULL + slot * 8, 16384);
                    s++;
                    return slot;
                };
                if (lane == 0) prefetch_tmap(&P.qkv);
                mbar_wait(bars + B_X + 3 * 8, 0);
#pragma unroll 1
                for (int p = 0; p < 12; p++) {
                    const int col = (p < 4 ? 512 : p < 8 ? 1024 : 0) + 64 * bj;
                    if (p == 6) mbar_wait(bars + B_XFREE, 0);
                    const uint32_t slot = acquire();
                    tma2d(sm + slot * STAGE_BYTES, &P.qkv, bars + B_FULL + slot * 8, col, (p & 3) * 128);
                }
#pragma unroll 1
                for (int q = 0; q < 4; q++) {
                    const uint32_t slot = acquire();
                    tma4d(sm + slot * STAGE_BYTES, &P.wo, bars + B_FULL + slot * 8, 64 * bj, q);
                }
                {
                    const uint32_t slot = acquire();
                    tma2d(sm + slot * STAGE_BYTES, &P.xm, bars + B_FULL + slot * 8, 64 * bj, bi * 128);
                }
                const int ofull = (bj & 1) * 32, oshort = (bj & 1) ? 0 : 192;
#pragma unroll 1
                for (int q = 0; q < 24; q++) {
                    if (q == 5) mbar_wait(bars + B_WG + LEAD * 128 + W_INH + 8, 0);
                    const uint32_t slot = acquire();
                    const int row = ((q & 6) == 0 ? bj ^ (q & 1) : (q + (bj & 6)) & 7) * 64;
                    tma2d(sm + slot * STAGE_BYTES, &P.wg, bars + B_FULL + slot * 8, 224 * bj + ofull + 64 * (q >> 3), row);
                    tma2d(sm + slot * STAGE_BYTES + 8192, &P.wu, bars + B_FULL + slot * 8, 224 * bj + ofull + 64 * (q >> 3), row);
                }
#pragma unroll 1
                for (int q = 0; q < 4; q++) {
                    const uint32_t slot = acquire();
                    for (int hh = 0; hh < 2; hh++) {
                        const int row = (q == 0 ? bj ^ hh : (2 * q + hh + (bj & 6)) & 7) * 64;
                        tma2d(sm + slot * STAGE_BYTES + hh * 4096, &P.wg2, bars + B_FULL + slot * 8, 224 * bj + oshort, row);
                        tma2d(sm + slot * STAGE_BYTES + 8192 + hh * 4096, &P.wu2, bars + B_FULL + slot * 8, 224 * bj + oshort, row);
                    }
                }
                const int c0 = 64 * bj, c1 = 64 * (bj ^ 1);
#pragma unroll 1
                for (int q = 0; q < 14; q++) {
                    if (q < 12) {
                        const int ck = q < 3 ? q : q / 3 - 1, r = q < 3 ? 0 : q - 3 * ck - 2;
                        const int row = 224 * ((bj + 2 * r) & 7) + ofull + 64 * ck;
                        const uint32_t slot = acquire();
                        tma2d(sm + slot * STAGE_BYTES, &P.wd, bars + B_FULL + slot * 8, c0, row);
                        tma2d(sm + slot * STAGE_BYTES + 8192, &P.wd, bars + B_FULL + slot * 8, c1, row);
                    } else {
                        const uint32_t slot = acquire();
                        for (int hh = 0; hh < 2; hh++) {
                            const int row = 224 * ((bj + 4 * (q - 12) + 2 * hh) & 7) + oshort;
                            tma2d(sm + slot * STAGE_BYTES + hh * 4096, &P.wd2, bars + B_FULL + slot * 8, c0, row);
                            tma2d(sm + slot * STAGE_BYTES + 8192 + hh * 4096, &P.wd2, bars + B_FULL + slot * 8, c1, row);
                        }
                    }
                }
            }
        } else {
            const unsigned ep = ld_ll1(&G->epoch[cta * 32]);
            if (warp == 9) {
                if (lane == 0) {
                    asm volatile("st.shared.u32 [%0], %1;" ::"r"(bars + SM_EPOCH), "r"(ep) : "memory");
                    mbar_arrive(bars + B_XFREE);
                    prefetch_tmap(&P.wo); prefetch_tmap(&P.wg); prefetch_tmap(&P.wu); prefetch_tmap(&P.wg2);
                    prefetch_tmap(&P.wu2); prefetch_tmap(&P.wd); prefetch_tmap(&P.wd2);
                }
                mbar_wait(bars + B_K, 0);
#pragma unroll 1
                for (int it = 0, r = 2; r < 8; it++) {
                    const int h = r >> 1, d = 1 + (r & 1);
                    if (bi < d) { r++; continue; }
                    const uint4* p = G->scr[ep & 1].kv + (cta - 8 * d) * 2048 + h * 256 + lane;
                    uint4 v[8];
                    uint32_t m = 0xffffffffu;
#pragma unroll
                    for (int b = 0; b < 8; b++) v[b] = ld_ll(p + b * 32);
#pragma unroll
                    for (int b = 0; b < 8; b++) m = umin4(m, v[b]);
                    if (!warp_bad(m) || it >= SPIN_LIMIT) {
#pragma unroll
                        for (int b = 0; b < 8; b++)
                            stsm4(sm + SM_K + (2 - d) * 4096 + lane * 16 + h * KVH + b * 512, v[b].x, v[b].y, v[b].z, v[b].w);
                        __syncwarp();
                        if (lane == 0) mbar_arrive(bars + B_K + h * 8);
                        r++;
                    }
                }
                {
                    constexpr int PER = sizeof(Scratch) / 16 / NCTA;
                    uint4* p = (uint4*)&G->scr[(ep & 1) ^ 1] + cta * PER + lane;
#pragma unroll 1
                    for (int k = 0; k < PER / 32; k += 2) {
                        stg128(p + k * 32, 0, 0, 0, 0);
                        stg128(p + k * 32 + 32, 0, 0, 0, 0);
                        __nanosleep(30);
                    }
                }
                {
#pragma unroll 1
                    for (int u = 0; u < 4; u++) {
                        mbar_wait(bars + B_PUB + u * 8, 0);
                        const uint32_t src = sm + SM_K + (u < 3 ? u : 5) * 8192, bytes = u < 3 ? 8192 : 4096;
                        bulk_s2g(G->hff + (cta * 8 + u) * 512, src, bytes);
                        bulk_s2g(G->hff + (cta * 8 + 4 + u) * 512, src + 49152, bytes);
                        asm volatile("cp.async.bulk.commit_group;" ::: "memory");
                        if (u == 3) {
                            asm volatile("cp.async.bulk.wait_group.read 0;" ::: "memory");
                            __syncwarp();
                            mbar_wait(bars + B_LVL, 0);
                            fill_a(G, sm, bars, bi, bj, 5, LEAD);
                            fill_a(G, sm, bars, bi, bj, 5, LEAD ^ 1);
                        }
                        if (u > 0) {
                            asm volatile("cp.async.bulk.wait_group 0;" ::: "memory");
                            __syncwarp();
                            if (lane == 0) flag_set(&G->flagF[cta * 32], 4 * ep + u);
                        }
                    }
                }
            } else {
                const int d = warp - 9;
                const uint32_t dkv = sm + SM_K + (2 - d) * 4096 + lane * 16;
                mbar_wait(bars + B_XFREE, 0);
                if (bi < d) {
#pragma unroll 1
                    for (int k = 0; k < 64; k++) sts128(dkv + (k >> 3) * (KVH / 2) + (k & 7) * 512, 0, 0, 0, 0);
                    __syncwarp();
                    if (lane < 8) mbar_arrive(bars + B_K + lane * 8);
                } else {
                    const uint4* skv = G->scr[ep & 1].kv + (cta - 8 * d) * 2048 + lane;
                    bool v0 = false;
#pragma unroll 1
                    for (int it = 0, r = 0; r < 5; it++) {
                        const bool probe = r == 0 && !v0 && !(it & 1);
                        const int u = probe ? 4 : (0x76540 >> (4 * r)) & 7;
                        uint4 v[8];
                        uint32_t m = 0xffffffffu;
#pragma unroll
                        for (int b = 0; b < 8; b++) v[b] = ld_ll(skv + u * 256 + b * 32);
#pragma unroll
                        for (int b = 0; b < 8; b++) m = umin4(m, v[b]);
                        if (!warp_bad(m) || it >= SPIN_LIMIT) {
#pragma unroll
                            for (int b = 0; b < 8; b++) {
                                stsm4(dkv + (u & 3) * KVH + (u >> 2) * (KVH / 2) + b * 512, v[b].x, v[b].y, v[b].z, v[b].w);
                            }
                            __syncwarp();
                            if (lane == 0) mbar_arrive(bars + B_K + u * 8);
                            if (probe) v0 = true;
                            else r += (r == 0 && v0) ? 2 : 1;
                        }
                    }
                }
                const int wg = d - 1;
                const uint32_t wb = bars + B_WG + wg * 128, ws = sm + SM_K + wg * 49152;
                const Scratch* scr = &G->scr[ep & 1];
                {
                    mbar_expect_w(wb + W_INO, 32768);
#pragma unroll 1
                    for (int u = 0; u < 2; u++) {
                        mbar_wait(u == 1 && wg == LEAD ? wb + W_H2 : bars + B_DEAD + u * 8, 0);
                        bulk_g2s(sm + SM_K + (wg == LEAD ? 0 : 32768) + u * 16384, scr->o + (bi * 2 + wg) * 4096 + u * 1024, 16384, wb + W_INO);
                    }
                }
                __syncwarp();
#pragma unroll 1
                for (int it = 0; it < SPIN_LIMIT; it++)
                    if (!warp_bad(ld_ll1((const uint32_t*)(scr->o + (bi * 2 + wg) * 4096 + 3072 + lane * 32 + 31) + 3))) break;
                if (lane == 0) mbar_arrive(wb + W_O3);
                {
                    const uint32_t* st = (const uint32_t*)(scr->stat + (bi * 8 + wg * 4) * 64 + lane * 2) + 3;
                    int u = 1;
#pragma unroll 1
                    for (int it = 0; u < 4; it++) {
                        uint32_t m = 0xffffffffu;
#pragma unroll
                        for (int b = 0; b < 2; b++) m = min(m, ld_ll1(st + (bj & 1) * 512 + b * 256));
                        const uint32_t bad = it >= SPIN_LIMIT ? 0u : __ballot_sync(0xffffffffu, m == 0);
#pragma unroll 1
                        for (; u < 4 && ((bad >> (8 * ((u + (bj >> 1)) & 3))) & 0xffu) == 0; u++) {
                            if (u == 1) mbar_wait(bars + B_DEAD + 16, 0);
                            bulk_g2s_pair(ws + (u - 1) * 16384 + (bj & 1) * 8192,
                                              scr->h + ((bi * 2 + wg) * 4 + ((u + (bj >> 1)) & 3)) * 1024 + (bj & 1) * 512, 8192, wb + W_INH + u * 8);
                        }
                    }
                }
                mbar_wait(wb + W_HDEAD, 0);
                if (wg == 1) {
                    mbar_wait(bars + B_LVL, 0);
                    mbar_wait(bars + B_PUB + 24, 0);
#pragma unroll 1
                    for (int q = 6; q < 14; q++) {
                        mbar_wait(bars + B_EMPTY + ((39 + q) & 7) * 8, ((39 + q) >> 3) & 1);
                        if (q == 8 || q == 12) mbar_wait(bars + B_LVL + (q >> 2) * 8 - 8, 0);
                        fill_a(G, sm, bars, bi, bj, q, LEAD);
                        fill_a(G, sm, bars, bi, bj, q, LEAD ^ 1);
                    }
                } else {
                    const unsigned* fl = &G->flagF[(bi * 8 + ((bj + 2 * lane) & 7)) * 32];
                    mbar_wait(bars + B_WG + 128 + W_HDEAD, 0);
#pragma unroll 1
                    for (int lvl = 1; lvl < 4; lvl++) {
#pragma unroll 1
                        for (int it = 0; it < 4 * SPIN_LIMIT; it++) {
                            const bool ok = lane >= 4 || (int)(ld_acquire(fl) - 4 * ep) >= lvl;
                            if (__all_sync(0xffffffffu, ok)) break;
                            __nanosleep(100);
                        }
                        if (lane == 0) mbar_arrive(bars + B_LVL + (lvl - 1) * 8);
                        __syncwarp();
                        if (lvl == 1) {
#pragma unroll 1
                            for (int u = 0; u < 4; u++) fill_a(G, sm, bars, bi, bj, 3 + (u >> 1), u & 1);
                        }
                    }
                }
            }
        }
    } else {
        asm volatile("setmaxnreg.inc.sync.aligned.u32 224;");
        const int w = warp, wg = warp >> 2, g = lane >> 2, cq = lane & 3;
        const Ctx c{sm, bars, lane, zero};
        unsigned epoch;
        Scratch* scr;
        uint32_t a[32][4];
        uint32_t qf[4][4];
        const uint32_t lsm = (w * 16 + (lane & 15)) * 128;
        {
            constexpr uint32_t ONES = 0x3f803f80u;
            float sa[4][4] = {}, qa[2][4] = {}, qb[2][4] = {};
            auto sums = [&](int kb) {
#pragma unroll
                for (int u = 0; u < 4; u++) vmma(sa[u], a[kb * 4 + u], ONES, ONES);
            };
            auto squares = [&](int kb) {
#pragma unroll
                for (int u = 0; u < 4; u++) {
                    const int t = kb * 4 + u;
                    vmma(qa[u & 1], a[t], a[t][0], a[t][2]);
                    vmma(qb[u & 1], a[t], a[t][1], a[t][3]);
                }
            };
#pragma unroll
            for (int kb = 0; kb < 8; kb++) {
                mbar_wait(bars + B_X + kb * 8, 0);
                const uint32_t base = sm + (kb < 6 ? SM_K + kb * 16384 : kb * STAGE_BYTES) + lsm;
#pragma unroll
                for (int u = 0; u < 4; u++) ldsm4(a[kb * 4 + u], base + (((2 * u + (lane >> 4)) ^ (lane & 7)) << 4));
                if (kb > 0) squares(kb - 1);
                sums(kb);
            }
            squares(7);
            const float m0 = (sa[0][0] + sa[1][0] + sa[2][0] + sa[3][0]) * (1.f / DM);
            const float m1 = (sa[0][2] + sa[1][2] + sa[2][2] + sa[3][2]) * (1.f / DM);
            if (lane == 0) mbar_arrive(tie(bars + B_XFREE, __float_as_uint(m0), c.zero));
            const uint32_t nm0 = pack_bf16(-m0, -m0), nm1 = pack_bf16(-m1, -m1);
            float accA[32], accB[32];
#pragma unroll
            for (int t = 0; t < 8; t++) centre(a[t], nm0, nm1);
            if (wg != LEAD) bar_sync(6, 256);
            stage_n64<0, 0, 2048, DESC_HI_128>(c, accA, a);
            if (wg == LEAD) bar_arrive(6, 256);
#pragma unroll
            for (int t = 8; t < 16; t++) centre(a[t], nm0, nm1);
            stage_n64<1, 8, 2048, DESC_HI_128>(c, accA, a);
#pragma unroll
            for (int t = 16; t < 32; t++) centre(a[t], nm0, nm1);
            float rs0, rs1;
            {
                const int dl = (lane & ~3) | (g >> 1);
                const float q0 = __shfl_sync(0xffffffffu, (g & 1) ? qa[0][1] + qa[1][1] : qa[0][0] + qa[1][0], dl);
                const float q1 = __shfl_sync(0xffffffffu, (g & 1) ? qb[0][3] + qb[1][3] : qb[0][2] + qb[1][2], dl);
                rs0 = rsqrtf(fmaxf(q0 * (1.f / DM) - m0 * m0, 0.f) + 1e-5f);
                rs1 = rsqrtf(fmaxf(q1 * (1.f / DM) - m1 * m1, 0.f) + 1e-5f);
            }
            wg_wait<1>(); release<0>(c);
            stage_n64<2, 16, 2048, DESC_HI_128>(c, accA, a);
            wg_wait<1>(); release<1>(c);
            stage_n64<3, 24, 2048, DESC_HI_128>(c, accA, a);
            wg_wait<1>(); release<2>(c);
            stage_n64<4, 0, 2048, DESC_HI_128>(c, accB, a);
            wg_wait<1>(); release<3>(c);
            fence_regs(accA);
            const float krs0 = rs0 * (0.25f * 1.4426950408889634f), krs1 = rs1 * (0.25f * 1.4426950408889634f);
            mbar_wait(bars + B_XFREE, 0);
            asm volatile("ld.shared.u32 %0, [%1];" : "=r"(epoch) : "r"(bars + SM_EPOCH) : "memory");
            scr = &G->scr[epoch & 1];
            uint4* const gkv = scr->kv + cta * 2048 + w * 32 + lane;
#pragma unroll
            for (int h = 0; h < 4; h++) {
                const uint32_t d01 = pack_bf16(accA[h * 8 + 0] * krs0, accA[h * 8 + 1] * krs0);
                const uint32_t d23 = pack_bf16(accA[h * 8 + 2] * krs1, accA[h * 8 + 3] * krs1);
                const uint32_t d45 = pack_bf16(accA[h * 8 + 4] * krs0, accA[h * 8 + 5] * krs0);
                const uint32_t d67 = nz(pack_bf16(accA[h * 8 + 6] * krs1, accA[h * 8 + 7] * krs1));
                st_ll(gkv + h * 256, d01, d45, d23, d67);
                stsm4(sm + SM_K + h * KVH + (16 + w) * 512 + lane * 16, d01, d45, d23, d67);
            }
            __syncwarp();
            if (lane < 4) mbar_arrive(bars + B_K + lane * 8);
            stage_n64<5, 8, 2048, DESC_HI_128>(c, accB, a);
            wg_wait<1>(); release<4>(c);
            stage_n64<6, 16, 2048, DESC_HI_128>(c, accB, a);
            wg_wait<1>(); release<5>(c);
            stage_n64<7, 24, 2048, DESC_HI_128>(c, accB, a);
            wg_wait<1>(); release<6>(c);
            auto epiV = [&]() {
                fence_regs(accB);
                release<7>(c);
#pragma unroll
                for (int h = 0; h < 4; h++) {
                    const uint32_t d01 = pack_bf16(accB[h * 8 + 0] * rs0, accB[h * 8 + 1] * rs0);
                    const uint32_t d23 = pack_bf16(accB[h * 8 + 2] * rs1, accB[h * 8 + 3] * rs1);
                    const uint32_t d45 = pack_bf16(accB[h * 8 + 4] * rs0, accB[h * 8 + 5] * rs0);
                    const uint32_t d67 = nz(pack_bf16(accB[h * 8 + 6] * rs1, accB[h * 8 + 7] * rs1));
                    st_ll(gkv + (4 + h) * 256, d01, d23, d45, d67);
                    stsm4(sm + SM_K + h * KVH + KVH / 2 + (16 + w) * 512 + lane * 16, d01, d23, d45, d67);
                }
                __syncwarp();
                if (lane < 4) mbar_arrive(bars + B_V + lane * 8);
            };
            wg_wait<0>();
            epiV();
            stage_n64<8, 0, 2048, DESC_HI_128>(c, accA, a);
            stage_n64<9, 8, 2048, DESC_HI_128>(c, accA, a);
            wg_wait<1>(); release<8>(c);
            stage_n64<10, 16, 2048, DESC_HI_128>(c, accA, a);
            wg_wait<1>(); release<9>(c);
            stage_n64<11, 24, 2048, DESC_HI_128>(c, accA, a);
            wg_wait<1>(); release<10>(c);
            wg_wait<0>(); release<11>(c);
            fence_regs(accA);
#pragma unroll
            for (int h = 0; h < 4; h++) {
                qf[h][0] = pack_bf16(accA[h * 8 + 0] * rs0, accA[h * 8 + 1] * rs0);
                qf[h][1] = pack_bf16(accA[h * 8 + 2] * rs1, accA[h * 8 + 3] * rs1);
                qf[h][2] = pack_bf16(accA[h * 8 + 4] * rs0, accA[h * 8 + 5] * rs0);
                qf[h][3] = pack_bf16(accA[h * 8 + 6] * rs1, accA[h * 8 + 7] * rs1);
            }
        }
        const int rec0 = ((bi * 2 + wg) * 16 + (w & 3)) * 256 + lane;
        attention(c, qf, bi, w, scr->o + rec0 + bj * 32, a, scr->o + rec0);
        const uint32_t wb = bars + B_WG + wg * 128, ws = sm + SM_K + wg * 49152;
        {
            const uint4* src = scr->o + rec0;
            __syncwarp();
            float acc[32];
            uint32_t xr[4][4];
            mbar_wait(bars + B_FULL, 0);
#pragma unroll
            for (int u = 0; u < 4; u++) ldsm4(xr[u], sm + lsm + (((2 * u + (lane >> 4)) ^ (lane & 7)) << 4));
            validate8<0>(a, src);
#pragma unroll
            for (int k = 0; k < 16; k++) { acc[2 * k] = bf_lo(xr[k >> 2][k & 3]); acc[2 * k + 1] = bf_hi(xr[k >> 2][k & 3]); }
            stage_n64<12, 0, 2048, DESC_HI_128, 1>(c, acc, a);
            if (lane < 2) mbar_arrive_remote(mapa(bars + B_XR, lane));
            validate8<8>(a, src + 1024);
            validate8<16>(a, src + 2048);
            bool got = mbar_test2(wb + W_O3, wb + W_O3);
            if (got) {
#pragma unroll
                for (int k = 0; k < 8; k++) ld_ll4(a[24 + k], src + 3072 + k * 32);
            }
            stage_n64<13, 8, 2048, DESC_HI_128>(c, acc, a);
            if (!got && mbar_test2(wb + W_O3, wb + W_O3)) {
                got = true;
#pragma unroll
                for (int k = 0; k < 8; k++) ld_ll4(a[24 + k], src + 3072 + k * 32);
            }
            wg_wait<1>(); release<12>(c);
            stage_n64<14, 16, 2048, DESC_HI_128>(c, acc, a);
            if (!got) {
                mbar_wait(wb + W_O3, 0);
#pragma unroll
                for (int k = 0; k < 8; k++) ld_ll4(a[24 + k], src + 3072 + k * 32);
            }
            wg_wait<1>(); release<13>(c);
            uint4* dst = scr->h + rec0 + (bj >> 1) * 1024 + (bj & 1) * 128;
            uint4* sdst = scr->stat + ((bi * 8 + w) * 8 + bj) * 8 + g;
            asm volatile("" : "+l"(dst), "+l"(sdst));
            mbar_wait(bars + B_FULL + 7 * 8, 1);
            validate8<24>(a, src + 3072);
            stage_n64<15, 24, 2048, DESC_HI_128, 2>(c, acc, a);
            wg_wait<1>(); release<14>(c);
            wg_wait<0>(); release<15>(c);
            if (lane < 2) mbar_arrive_remote(mapa(bars + B_DEAD + 16, lane));
            fence_regs(acc);
#pragma unroll
            for (int k = 0; k < 4; k++) {
#pragma unroll
                for (int e = 0; e < 4; e++) a[k][e] = pack_bf16(acc[8 * k + 2 * e], acc[8 * k + 2 * e + 1]);
                a[k][3] = nz(a[k][3]);
                st_ll(dst + k * 32, a[k][0], a[k][1], a[k][2], a[k][3]);
            }
            fence_regs(acc);
            mbar_wait(bars + B_XR, 0);
            float s0 = 0.f, s1 = 0.f, q0 = 0.f, q1 = 0.f;
#pragma unroll
            for (int b = 0; b < 8; b++) {
                s0 += acc[4 * b] + acc[4 * b + 1];
                s1 += acc[4 * b + 2] + acc[4 * b + 3];
                q0 = fmaf(acc[4 * b], acc[4 * b], fmaf(acc[4 * b + 1], acc[4 * b + 1], q0));
                q1 = fmaf(acc[4 * b + 2], acc[4 * b + 2], fmaf(acc[4 * b + 3], acc[4 * b + 3], q1));
            }
#pragma unroll
            for (int m = 1; m <= 2; m <<= 1) {
                s0 += __shfl_xor_sync(0xffffffffu, s0, m); q0 += __shfl_xor_sync(0xffffffffu, q0, m);
                s1 += __shfl_xor_sync(0xffffffffu, s1, m); q1 += __shfl_xor_sync(0xffffffffu, q1, m);
            }
            if (cq == 0) st_ll(sdst, __float_as_uint(s0), __float_as_uint(q0), __float_as_uint(s1), nz(__float_as_uint(q1)));
            mbar_wait(bars + B_XR, 0);
            const uint32_t hdst = mapa(sm + w * 2048 + lane * 16, (bj & 1) ^ 1), hbar = mapa(bars + B_XCH + w * 8, (bj & 1) ^ 1);
#pragma unroll
            for (int k = 0; k < 4; k++) st_async4(hdst + k * 512, hbar, a[k][0], a[k][1], a[k][2], a[k][3]);
        }
        float r20, r21;
        uint32_t nm0, nm1;
        const uint4* hsrc = scr->h + rec0;
        {
            const uint4* st = scr->stat + ((bi * 8 + w) * 8 + cq) * 8 + g;
            uint4 sa, sb;
#pragma unroll 1
            for (int it = 0;; it++) {
                sa = ld_ll(st);
                sb = ld_ll(st + 32);
                if (!warp_bad(umin4(umin4(0xffffffffu, sa), sb)) || it >= SPIN_LIMIT) break;
            }
            mbar_wait_cluster(bars + B_XCH + w * 8, 0);
#pragma unroll
            for (int k = 0; k < 4; k++) lds4(a[4 + k], sm + w * 2048 + lane * 16 + k * 512);
            float s0 = __uint_as_float(sa.x) + __uint_as_float(sb.x), q0 = __uint_as_float(sa.y) + __uint_as_float(sb.y);
            float s1 = __uint_as_float(sa.z) + __uint_as_float(sb.z), q1 = __uint_as_float(sa.w) + __uint_as_float(sb.w);
#pragma unroll
            for (int m = 1; m <= 2; m <<= 1) {
                s0 += __shfl_xor_sync(0xffffffffu, s0, m); q0 += __shfl_xor_sync(0xffffffffu, q0, m);
                s1 += __shfl_xor_sync(0xffffffffu, s1, m); q1 += __shfl_xor_sync(0xffffffffu, q1, m);
            }
            const float m0 = s0 * (1.f / DM), m1 = s1 * (1.f / DM);
            r20 = __fdividef(0.5f, fmaxf(q0 * (1.f / DM) - m0 * m0, 0.f) + 1e-5f);
            r21 = __fdividef(0.5f, fmaxf(q1 * (1.f / DM) - m1 * m1, 0.f) + 1e-5f);
            nm0 = pack_bf16(-m0, -m0); nm1 = pack_bf16(-m1, -m1);
            if (lane == 0) {
                mbar_expect(bars + B_XCH + w * 8, 2048);
                mbar_arrive(tie(bars + B_EMPTY, a[4][0] ^ a[5][0] ^ a[6][0] ^ a[7][0], c.zero));
            }
        }
        const uint32_t hff = ws + (w & 3) * 512 + ((lane >> 3) & 1) * 256 + (lane >> 4) * 128 + (lane & 7) * 16;
#pragma unroll 1
        for (int ch = 0; ch < 3; ch++) {
            float acc[64];
#pragma unroll
            for (int q = 0; q < 8; q++) {
                if (ch == 0) {
                    const uint32_t hs = ws + (w & 3) * 4096 + lane * 16;
                    if (q == 1 || q == 3 || q == 5) mbar_wait(wb + W_INH + ((q + 1) / 2) * 8, 0);
                    if (q == 1) lds8<8>(a, hs);
                    if (q == 2) check8<8>(a, hs, hsrc + (((bj >> 1) + 1) & 3) * 1024);
                    if (q == 3) lds8<16>(a, hs + 16384);
                    if (q == 4) check8<16>(a, hs + 16384, hsrc + (((bj >> 1) + 2) & 3) * 1024);
                    if (q == 5) lds8<24>(a, hs + 32768);
                    if (q == 6) check8<24>(a, hs + 32768, hsrc + (((bj >> 1) + 3) & 3) * 1024);
                    if ((q & 1) == 0) {
#pragma unroll
                        for (int k = 0; k < 8; k++) centre(a[q * 4 + k], nm0, nm1);
                    }
                    if (q == 6 && lane == 0) mbar_arrive(tie(wb + W_HDEAD, a[24][0] ^ a[25][0] ^ a[26][0] ^ a[27][0] ^ a[28][0] ^ a[29][0] ^ a[30][0] ^ a[31][0], c.zero));
                    if (q == 5 && wg != LEAD) bar_sync(5, 256);
                }
                mbar_wait(bars + B_FULL + ((q + 1) & 7) * 8, (ch + (q == 7)) & 1);
                wg_fence();
                constexpr uint32_t lo0 = (SMD >> 4) | DESC_LBO;
#pragma unroll
                for (int k = 0; k < 4; k++)
                    wgmma_n128(acc, a[q * 4 + k], make_desc(lo0 + ((q + 1) & 7) * 1024 + k * 128, DESC_HI_128), (q | k) != 0);
                wg_commit();
                if (q == 7 && ch == 0 && wg == LEAD) bar_arrive(5, 256);
                if (q > 0) {
                    wg_wait<1>();
                    if (lane == 0) mbar_arrive(bars + B_EMPTY + q * 8);
                }
            }
            wg_wait<0>();
            fence_regs(acc);
            if (lane == 0) mbar_arrive(bars + B_EMPTY);
            if (ch == 0) mbar_wait(wb + W_HDEAD, 0);
#pragma unroll
            for (int k = 0; k < 4; k++) {
                uint32_t f[4];
#pragma unroll
                for (int e = 0; e < 4; e++) {
                    const int i0 = k * 8 + e * 2;
                    f[e] = pack_bf16(relu2(acc[i0]) * acc[32 + i0], relu2(acc[i0 + 1]) * acc[32 + i0 + 1]);
                }
                stsm4(hff + ch * 8192 + k * 2048, f[0], f[1], f[2], f[3]);
            }
            asm volatile("fence.proxy.async.shared::cta;" ::: "memory");
            __syncwarp();
            if (lane == 0) mbar_arrive(bars + B_PUB + ch * 8);
        }
        uint32_t hres[4][4];
#pragma unroll
        for (int k = 0; k < 4; k++) ld_cg4(hres[k], hsrc + (bj >> 1) * 1024 + (bj & 1) * 128 + k * 32);
        {
            float acc[32];
            stage_n64<41, 0, 1024, DESC_HI_64>(c, acc, a);
            stage_n64<42, 8, 1024, DESC_HI_64>(c, acc, a);
            wg_wait<1>(); release<41>(c);
            stage_n64<43, 16, 1024, DESC_HI_64>(c, acc, a);
            wg_wait<1>(); release<42>(c);
            stage_n64<44, 24, 1024, DESC_HI_64>(c, acc, a);
            wg_wait<1>(); release<43>(c);
            wg_wait<0>(); release<44>(c);
            fence_regs(acc);
#pragma unroll
            for (int k = 0; k < 2; k++) {
                uint32_t f[4];
#pragma unroll
                for (int e = 0; e < 4; e++) {
                    const int i0 = k * 8 + e * 2;
                    f[e] = pack_bf16(relu2(acc[i0]) * acc[16 + i0], relu2(acc[i0 + 1]) * acc[16 + i0 + 1]);
                }
                stsm4(hff + 5 * 8192 + k * 2048, f[0], f[1], f[2], f[3]);
            }
            asm volatile("fence.proxy.async.shared::cta;" ::: "memory");
            __syncwarp();
            if (lane == 0) mbar_arrive(bars + B_PUB + 24);
        }
        {
            float acc[64];
            float hf[32] = {};
            uint32_t xch = 0, rdst = 0, rbar = 0, ost = 0, old = 0;
            uint4* og = nullptr;
            mbar_wait(bars + B_PUB + 16, 0);
            const uint32_t alo = ((SMD + SM_K + wg * 49152) >> 4) | ((128 >> 4) << 16);
#pragma unroll 1
            for (int q = 0; q < 14; q++) {
                const int s = 45 + q, slot = s & 7, sl = q < 6 ? q : q < 12 ? q - 6 : q - 12;
                if (q >= 3) mbar_wait(wb + W_INA + sl * 8, q >= 9);
                mbar_wait(bars + B_FULL + slot * 8, (s >> 3) & 1);
                wg_fence();
                const uint32_t lo = ((SMD + slot * STAGE_BYTES) >> 4) | DESC_LBO;
#pragma unroll
                for (int k = 0; k < 4; k++)
                    wgmma_n128_ss(acc, make_desc(alo + sl * 512 + k * 128, 256 >> 4), make_desc(lo + k * 128, DESC_HI_128), (q | k) != 0);
                wg_commit();
                wg_wait<1>();
                if (q > 0 && q <= 8 && lane == 0) mbar_arrive(bars + B_EMPTY + ((s - 1) & 7) * 8);
                if (q == 10) asm volatile("barrier.cluster.arrive.relaxed.aligned;" ::: "memory");
                if (q == 1) {
#pragma unroll
                    for (int k = 0; k < 16; k++) { hf[2 * k] = bf_lo(hres[k >> 2][k & 3]); hf[2 * k + 1] = bf_hi(hres[k >> 2][k & 3]); }
                    xch = ws + 2 * 8192 + (w & 3) * 2048 + lane * 16;
                    rdst = mapa(xch, (bj & 1) ^ 1);
                    rbar = mapa(bars + B_XCH + w * 8, (bj & 1) ^ 1);
                    ost = ws + 3 * 8192 + (w & 3) * 2048 + (lane & 15) * 128 + (((lane >> 4) ^ (lane & 7)) << 4);
                    old = ws + 3 * 8192 + (w & 3) * 2048 + (lane >> 3) * 128 + (((lane & 7) ^ (lane >> 3)) << 4);
                    og = outp + (bi * 128 + w * 16 + (lane >> 3)) * 64 + bj * 8 + (lane & 7);
                }
            }
            asm volatile("barrier.cluster.wait.acquire.aligned;" ::: "memory");
            wg_wait<0>();
            fence_regs(acc);
#pragma unroll
            for (int b = 0; b < 4; b++)
                st_async4(rdst + b * 512, rbar, pack_bf16(acc[32 + 8 * b], acc[33 + 8 * b]), pack_bf16(acc[34 + 8 * b], acc[35 + 8 * b]),
                          pack_bf16(acc[36 + 8 * b], acc[37 + 8 * b]), pack_bf16(acc[38 + 8 * b], acc[39 + 8 * b]));
#pragma unroll
            for (int k = 0; k < 32; k++) acc[k] = fmaf(acc[k], (k & 2) ? r21 : r20, hf[k]);
            mbar_wait_cluster(bars + B_XCH + w * 8, 1);
            uint4 u[4];
#pragma unroll
            for (int b = 0; b < 4; b++) u[b] = lds128(xch + b * 512);
#pragma unroll
            for (int b = 0; b < 4; b++)
                stsm4(ost ^ (b << 5), pack_bf16(fmaf(bf_lo(u[b].x), r20, acc[8 * b]), fmaf(bf_hi(u[b].x), r20, acc[8 * b + 1])),
                      pack_bf16(fmaf(bf_lo(u[b].y), r21, acc[8 * b + 2]), fmaf(bf_hi(u[b].y), r21, acc[8 * b + 3])),
                      pack_bf16(fmaf(bf_lo(u[b].z), r20, acc[8 * b + 4]), fmaf(bf_hi(u[b].z), r20, acc[8 * b + 5])),
                      pack_bf16(fmaf(bf_lo(u[b].w), r21, acc[8 * b + 6]), fmaf(bf_hi(u[b].w), r21, acc[8 * b + 7])));
            __syncwarp();
#pragma unroll
            for (int b = 0; b < 4; b++) u[b] = lds128((old ^ ((b & 1) << 6)) + b * 512);
#pragma unroll
            for (int b = 0; b < 4; b++) stg128(og + b * 256, u[b].x, u[b].y, u[b].z, u[b].w);
        }
        if (tid == 0) G->epoch[cta * 32] = epoch + 1;
    }
}

typedef CUresult (*EncodeFn)(CUtensorMap*, CUtensorMapDataType, cuuint32_t, void*, const cuuint64_t*, const cuuint64_t*,
                             const cuuint32_t*, const cuuint32_t*, CUtensorMapInterleave, CUtensorMapSwizzle,
                             CUtensorMapL2promotion, CUtensorMapFloatOOBfill);

void make2d(EncodeFn enc, CUtensorMap* tm, const void* ptr, int cols, int rows, int bc, int br, CUtensorMapSwizzle sw) {
    cuuint64_t gd[2] = {(cuuint64_t)cols, (cuuint64_t)rows};
    cuuint64_t gs[1] = {(cuuint64_t)cols * 2};
    cuuint32_t bd[2] = {(cuuint32_t)bc, (cuuint32_t)br};
    cuuint32_t es[2] = {1, 1};
    enc(tm, CU_TENSOR_MAP_DATA_TYPE_BFLOAT16, 2, const_cast<void*>(ptr), gd, gs, bd, es, CU_TENSOR_MAP_INTERLEAVE_NONE, sw,
        CU_TENSOR_MAP_L2_PROMOTION_L2_128B, CU_TENSOR_MAP_FLOAT_OOB_FILL_NONE);
}

}

extern "C" void kernel_launch(void* const* d_in, const int* in_sizes, int n_in, void* d_out, int out_size) {
    (void)in_sizes; (void)n_in; (void)out_size;
    static EncodeFn enc = nullptr;
    static Global* gmem = nullptr;
    if (!enc) {
        cudaGetSymbolAddress((void**)&gmem, g_mem);
        void* fn = nullptr;
        cudaDriverEntryPointQueryResult qr;
        cudaGetDriverEntryPoint("cuTensorMapEncodeTiled", &fn, cudaEnableDefault, &qr);
        enc = (EncodeFn)fn;
        cudaFuncSetAttribute(fused_block_kernel, cudaFuncAttributeMaxDynamicSharedMemorySize, SMEM_BYTES);
    }
    Params P;
    make2d(enc, &P.xm, d_in[0], DM, 2048, 64, 128, CU_TENSOR_MAP_SWIZZLE_128B);
    make2d(enc, &P.qkv, d_in[1], 3 * DM, DM, 64, 128, CU_TENSOR_MAP_SWIZZLE_128B);
    {
        cuuint64_t gd[4] = {DM, 16, 4, 8};
        cuuint64_t gs[3] = {DM * 2, 16 * DM * 2, 64 * DM * 2};
        cuuint32_t bd[4] = {64, 16, 1, 8};
        cuuint32_t es[4] = {1, 1, 1, 1};
        enc(&P.wo, CU_TENSOR_MAP_DATA_TYPE_BFLOAT16, 4, d_in[2], gd, gs, bd, es, CU_TENSOR_MAP_INTERLEAVE_NONE,
            CU_TENSOR_MAP_SWIZZLE_128B, CU_TENSOR_MAP_L2_PROMOTION_L2_128B, CU_TENSOR_MAP_FLOAT_OOB_FILL_NONE);
    }
    make2d(enc, &P.wg, d_in[4], FF, DM, 64, 64, CU_TENSOR_MAP_SWIZZLE_128B);
    make2d(enc, &P.wu, d_in[5], FF, DM, 64, 64, CU_TENSOR_MAP_SWIZZLE_128B);
    make2d(enc, &P.wg2, d_in[4], FF, DM, 32, 64, CU_TENSOR_MAP_SWIZZLE_64B);
    make2d(enc, &P.wu2, d_in[5], FF, DM, 32, 64, CU_TENSOR_MAP_SWIZZLE_64B);
    make2d(enc, &P.wd, d_in[6], DM, FF, 64, 64, CU_TENSOR_MAP_SWIZZLE_128B);
    make2d(enc, &P.wd2, d_in[6], DM, FF, 64, 32, CU_TENSOR_MAP_SWIZZLE_128B);
    fused_block_kernel<<<NCTA, 384, SMEM_BYTES>>>(gmem, 0u, (uint4*)d_out, P);
}
```
